```python
import torch

def _softmax(x, axis=-1):
    return torch.softmax(x, dim=axis)
def _gelu(x):
    return torch.nn.functional.gelu(x, approximate="tanh")
def _silu(x):
    return torch.nn.functional.silu(x)
def _sigmoid(x):
    return torch.sigmoid(x)
def _layernorm(x, axis=-1, eps=1e-5):
    m = x.mean(dim=axis, keepdim=True)
    v = x.var(dim=axis, keepdim=True, unbiased=False)
    return (x - m) / torch.sqrt(v + eps)
def _scatter_add(tgt, idx, src, axis=0):
    return tgt.clone().index_add_(axis, idx, src)
def _segment_sum(src, seg, n):
    out = torch.zeros((n,) + src.shape[1:], dtype=src.dtype)
    return out.index_add_(0, seg, src)
def _pad(x, pw):
    flat = tuple(v for pair in reversed(pw) for v in pair)
    return torch.nn.functional.pad(x, flat)

kernel_name = 'gated_mix__softmax_full_mha__geglu_ffn__prompt'

def setup_inputs():

    _w = (lambda a: (lambda t: t.to(torch.bfloat16) if t.is_floating_point() else t)(torch.as_tensor(a)))
    def _A_setup():
        B, S, D = 1, 2048, 576
        return {
            "x": _w((lambda *s: torch.randn(*s, dtype=torch.bfloat16) * 0.05)(B, S, D)),
            "wqkv": _w((lambda *s: torch.randn(*s, dtype=torch.bfloat16) * 0.8)(D, 3 * D)),
            "wo": _w((lambda *s: torch.randn(*s, dtype=torch.bfloat16) * 0.05)(D, D)),
        }
    _A_in = _A_setup()

    def _B_setup():
        B, S, D, F = 1, 2048, 576, 4608
        return {
            "x": _w((lambda *s: torch.randn(*s, dtype=torch.bfloat16) * 0.05)(B, S, D)),
            "w_gate": _w((lambda *s: torch.randn(*s, dtype=torch.bfloat16) * 0.1)(D, F)),
            "w_up": _w((lambda *s: torch.randn(*s, dtype=torch.bfloat16) * 0.1)(D, F)),
            "w_down": _w((lambda *s: torch.randn(*s, dtype=torch.bfloat16) * 0.1)(F, D)),
        }
    _B_in = _B_setup()

    return {
        "A_x": _A_in["x"],
        "A_wqkv": _A_in["wqkv"],
        "A_wo": _A_in["wo"],
        "B_x": _B_in["x"],
        "B_w_gate": _B_in["w_gate"],
        "B_w_up": _B_in["w_up"],
        "B_w_down": _B_in["w_down"],
        "gate_w": _w((lambda *s: torch.randn(*s, dtype=torch.bfloat16) * 0.05)(576) * 16.0),
    }

def reference(A_x, A_wqkv, A_wo, B_x, B_w_gate, B_w_up, B_w_down, gate_w):
    def _A_ref(x, wqkv, wo):
        B, S, D = x.shape
        H = 32; Dh = D // H
        qkv = (lambda x, *d: x.permute(*d))((x @ wqkv).reshape(B, S, 3, H, Dh), 2, 0, 3, 1, 4)
        q, k, v = qkv[0], qkv[1], qkv[2]
        scale = Dh ** -0.5
        scores = torch.einsum("bhqd,bhkd->bhqk", q, k) * scale
        p = _softmax(scores, axis=-1)
        o = torch.einsum("bhqk,bhkd->bhqd", p, v)
        return (lambda x, *d: x.permute(*d))(o, 0, 2, 1, 3).reshape(B, S, D) @ wo

    def _B_ref(x, w_gate, w_up, w_down):
        return (_gelu(x @ w_gate) * (x @ w_up)) @ w_down

    x = A_x
    g = _sigmoid((x * gate_w).sum(-1, keepdims=True))
    a = _A_ref(x, A_wqkv, A_wo)
    b = _B_ref(x, B_w_gate, B_w_up, B_w_down)
    return g * a + (1 - g) * b
```

```cpp
#include <cuda_runtime.h>
#include <cuda_bf16.h>
#include <cuda.h>
#include <stdint.h>
#include <stdio.h>

namespace {

template <int TB, int OB> __device__ __forceinline__ void wgmma_rs_n24(float (&d)[12], uint32_t a0, uint32_t a1, uint32_t a2, uint32_t a3, uint64_t db, int scaleD) {
  asm volatile("{\n.reg .b64 b;\nadd.s64 b, %16, %18;\n.reg .pred p;\nsetp.ne.b32 p, %19, 0;\n"
    "wgmma.mma_async.sync.aligned.m64n24k16.f32.bf16.bf16 "
    "{%0, %1, %2, %3, %4, %5, %6, %7, %8, %9, %10, %11}, {%12,%13,%14,%15}, b, p, 1, 1, %17;\n}\n"
    : "+f"(d[0]), "+f"(d[1]), "+f"(d[2]), "+f"(d[3]), "+f"(d[4]), "+f"(d[5]), "+f"(d[6]), "+f"(d[7]), "+f"(d[8]), "+f"(d[9]), "+f"(d[10]), "+f"(d[11])
    : "r"(a0), "r"(a1), "r"(a2), "r"(a3), "l"(db), "n"(TB), "n"(OB), "r"(scaleD));
}
template <int TB, int OB> __device__ __forceinline__ void wgmma_rs0_n64(float (&d)[32], uint32_t a0, uint32_t a1, uint32_t a2, uint32_t a3, uint64_t db) {
  asm volatile("{\n.reg .b64 b;\nadd.s64 b, %36, %38;\n"
    "wgmma.mma_async.sync.aligned.m64n64k16.f32.bf16.bf16 "
    "{%0, %1, %2, %3, %4, %5, %6, %7, %8, %9, %10, %11, %12, %13, %14, %15, %16, %17, %18, %19, %20, %21, %22, %23, %24, %25, %26, %27, %28, %29, %30, %31}, {%32,%33,%34,%35}, b, 0, 1, 1, %37;\n}\n"
    : "=f"(d[0]), "=f"(d[1]), "=f"(d[2]), "=f"(d[3]), "=f"(d[4]), "=f"(d[5]), "=f"(d[6]), "=f"(d[7]), "=f"(d[8]), "=f"(d[9]), "=f"(d[10]), "=f"(d[11]), "=f"(d[12]), "=f"(d[13]), "=f"(d[14]), "=f"(d[15]), "=f"(d[16]), "=f"(d[17]), "=f"(d[18]), "=f"(d[19]), "=f"(d[20]), "=f"(d[21]), "=f"(d[22]), "=f"(d[23]), "=f"(d[24]), "=f"(d[25]), "=f"(d[26]), "=f"(d[27]), "=f"(d[28]), "=f"(d[29]), "=f"(d[30]), "=f"(d[31])
    : "r"(a0), "r"(a1), "r"(a2), "r"(a3), "l"(db), "n"(TB), "n"(OB));
}
template <int TB, int OB> __device__ __forceinline__ void wgmma_rs1_n24(float (&d)[12], uint32_t a0, uint32_t a1, uint32_t a2, uint32_t a3, uint64_t db) {
  asm volatile("{\n.reg .b64 b;\nadd.s64 b, %16, %18;\n"
    "wgmma.mma_async.sync.aligned.m64n24k16.f32.bf16.bf16 "
    "{%0, %1, %2, %3, %4, %5, %6, %7, %8, %9, %10, %11}, {%12,%13,%14,%15}, b, 1, 1, 1, %17;\n}\n"
    : "+f"(d[0]), "+f"(d[1]), "+f"(d[2]), "+f"(d[3]), "+f"(d[4]), "+f"(d[5]), "+f"(d[6]), "+f"(d[7]), "+f"(d[8]), "+f"(d[9]), "+f"(d[10]), "+f"(d[11])
    : "r"(a0), "r"(a1), "r"(a2), "r"(a3), "l"(db), "n"(TB), "n"(OB));
}
template <int TB, int OB> __device__ __forceinline__ void wgmma_rs1_n64(float (&d)[32], uint32_t a0, uint32_t a1, uint32_t a2, uint32_t a3, uint64_t db) {
  asm volatile("{\n.reg .b64 b;\nadd.s64 b, %36, %38;\n"
    "wgmma.mma_async.sync.aligned.m64n64k16.f32.bf16.bf16 "
    "{%0, %1, %2, %3, %4, %5, %6, %7, %8, %9, %10, %11, %12, %13, %14, %15, %16, %17, %18, %19, %20, %21, %22, %23, %24, %25, %26, %27, %28, %29, %30, %31}, {%32,%33,%34,%35}, b, 1, 1, 1, %37;\n}\n"
    : "+f"(d[0]), "+f"(d[1]), "+f"(d[2]), "+f"(d[3]), "+f"(d[4]), "+f"(d[5]), "+f"(d[6]), "+f"(d[7]), "+f"(d[8]), "+f"(d[9]), "+f"(d[10]), "+f"(d[11]), "+f"(d[12]), "+f"(d[13]), "+f"(d[14]), "+f"(d[15]), "+f"(d[16]), "+f"(d[17]), "+f"(d[18]), "+f"(d[19]), "+f"(d[20]), "+f"(d[21]), "+f"(d[22]), "+f"(d[23]), "+f"(d[24]), "+f"(d[25]), "+f"(d[26]), "+f"(d[27]), "+f"(d[28]), "+f"(d[29]), "+f"(d[30]), "+f"(d[31])
    : "r"(a0), "r"(a1), "r"(a2), "r"(a3), "l"(db), "n"(TB), "n"(OB));
}
template <int TB, int OA, int OB, int R0 = 0, int NA> __device__ __forceinline__ void wgmma_ss_n256(float (&d)[NA], uint64_t da, uint64_t db, int scaleD) {
  asm volatile("{\n.reg .b64 a, b;\nadd.s64 a, %128, %131;\nadd.s64 b, %129, %132;\n.reg .pred p;\nsetp.ne.b32 p, %133, 0;\n"
    "wgmma.mma_async.sync.aligned.m64n256k16.f32.bf16.bf16 "
    "{%0, %1, %2, %3, %4, %5, %6, %7, %8, %9, %10, %11, %12, %13, %14, %15, %16, %17, %18, %19, %20, %21, %22, %23, %24, %25, %26, %27, %28, %29, %30, %31, %32, %33, %34, %35, %36, %37, %38, %39, %40, %41, %42, %43, %44, %45, %46, %47, %48, %49, %50, %51, %52, %53, %54, %55, %56, %57, %58, %59, %60, %61, %62, %63, %64, %65, %66, %67, %68, %69, %70, %71, %72, %73, %74, %75, %76, %77, %78, %79, %80, %81, %82, %83, %84, %85, %86, %87, %88, %89, %90, %91, %92, %93, %94, %95, %96, %97, %98, %99, %100, %101, %102, %103, %104, %105, %106, %107, %108, %109, %110, %111, %112, %113, %114, %115, %116, %117, %118, %119, %120, %121, %122, %123, %124, %125, %126, %127}, a, b, p, 1, 1, 0, %130;\n}\n"
    : "+f"(d[R0 + 0]), "+f"(d[R0 + 1]), "+f"(d[R0 + 2]), "+f"(d[R0 + 3]), "+f"(d[R0 + 4]), "+f"(d[R0 + 5]), "+f"(d[R0 + 6]), "+f"(d[R0 + 7]), "+f"(d[R0 + 8]), "+f"(d[R0 + 9]), "+f"(d[R0 + 10]), "+f"(d[R0 + 11]), "+f"(d[R0 + 12]), "+f"(d[R0 + 13]), "+f"(d[R0 + 14]), "+f"(d[R0 + 15]), "+f"(d[R0 + 16]), "+f"(d[R0 + 17]), "+f"(d[R0 + 18]), "+f"(d[R0 + 19]), "+f"(d[R0 + 20]), "+f"(d[R0 + 21]), "+f"(d[R0 + 22]), "+f"(d[R0 + 23]), "+f"(d[R0 + 24]), "+f"(d[R0 + 25]), "+f"(d[R0 + 26]), "+f"(d[R0 + 27]), "+f"(d[R0 + 28]), "+f"(d[R0 + 29]), "+f"(d[R0 + 30]), "+f"(d[R0 + 31]), "+f"(d[R0 + 32]), "+f"(d[R0 + 33]), "+f"(d[R0 + 34]), "+f"(d[R0 + 35]), "+f"(d[R0 + 36]), "+f"(d[R0 + 37]), "+f"(d[R0 + 38]), "+f"(d[R0 + 39]), "+f"(d[R0 + 40]), "+f"(d[R0 + 41]), "+f"(d[R0 + 42]), "+f"(d[R0 + 43]), "+f"(d[R0 + 44]), "+f"(d[R0 + 45]), "+f"(d[R0 + 46]), "+f"(d[R0 + 47]), "+f"(d[R0 + 48]), "+f"(d[R0 + 49]), "+f"(d[R0 + 50]), "+f"(d[R0 + 51]), "+f"(d[R0 + 52]), "+f"(d[R0 + 53]), "+f"(d[R0 + 54]), "+f"(d[R0 + 55]), "+f"(d[R0 + 56]), "+f"(d[R0 + 57]), "+f"(d[R0 + 58]), "+f"(d[R0 + 59]), "+f"(d[R0 + 60]), "+f"(d[R0 + 61]), "+f"(d[R0 + 62]), "+f"(d[R0 + 63]), "+f"(d[R0 + 64]), "+f"(d[R0 + 65]), "+f"(d[R0 + 66]), "+f"(d[R0 + 67]), "+f"(d[R0 + 68]), "+f"(d[R0 + 69]), "+f"(d[R0 + 70]), "+f"(d[R0 + 71]), "+f"(d[R0 + 72]), "+f"(d[R0 + 73]), "+f"(d[R0 + 74]), "+f"(d[R0 + 75]), "+f"(d[R0 + 76]), "+f"(d[R0 + 77]), "+f"(d[R0 + 78]), "+f"(d[R0 + 79]), "+f"(d[R0 + 80]), "+f"(d[R0 + 81]), "+f"(d[R0 + 82]), "+f"(d[R0 + 83]), "+f"(d[R0 + 84]), "+f"(d[R0 + 85]), "+f"(d[R0 + 86]), "+f"(d[R0 + 87]), "+f"(d[R0 + 88]), "+f"(d[R0 + 89]), "+f"(d[R0 + 90]), "+f"(d[R0 + 91]), "+f"(d[R0 + 92]), "+f"(d[R0 + 93]), "+f"(d[R0 + 94]), "+f"(d[R0 + 95]), "+f"(d[R0 + 96]), "+f"(d[R0 + 97]), "+f"(d[R0 + 98]), "+f"(d[R0 + 99]), "+f"(d[R0 + 100]), "+f"(d[R0 + 101]), "+f"(d[R0 + 102]), "+f"(d[R0 + 103]), "+f"(d[R0 + 104]), "+f"(d[R0 + 105]), "+f"(d[R0 + 106]), "+f"(d[R0 + 107]), "+f"(d[R0 + 108]), "+f"(d[R0 + 109]), "+f"(d[R0 + 110]), "+f"(d[R0 + 111]), "+f"(d[R0 + 112]), "+f"(d[R0 + 113]), "+f"(d[R0 + 114]), "+f"(d[R0 + 115]), "+f"(d[R0 + 116]), "+f"(d[R0 + 117]), "+f"(d[R0 + 118]), "+f"(d[R0 + 119]), "+f"(d[R0 + 120]), "+f"(d[R0 + 121]), "+f"(d[R0 + 122]), "+f"(d[R0 + 123]), "+f"(d[R0 + 124]), "+f"(d[R0 + 125]), "+f"(d[R0 + 126]), "+f"(d[R0 + 127])
    : "l"(da), "l"(db), "n"(TB), "n"(OA), "n"(OB), "r"(scaleD));
}
template <int TB, int OA, int OB, int R0 = 0, int NA> __device__ __forceinline__ void wgmma_ss0_n256(float (&d)[NA], uint64_t da, uint64_t db) {
  asm volatile("{\n.reg .b64 a, b;\nadd.s64 a, %128, %131;\nadd.s64 b, %129, %132;\n"
    "wgmma.mma_async.sync.aligned.m64n256k16.f32.bf16.bf16 "
    "{%0, %1, %2, %3, %4, %5, %6, %7, %8, %9, %10, %11, %12, %13, %14, %15, %16, %17, %18, %19, %20, %21, %22, %23, %24, %25, %26, %27, %28, %29, %30, %31, %32, %33, %34, %35, %36, %37, %38, %39, %40, %41, %42, %43, %44, %45, %46, %47, %48, %49, %50, %51, %52, %53, %54, %55, %56, %57, %58, %59, %60, %61, %62, %63, %64, %65, %66, %67, %68, %69, %70, %71, %72, %73, %74, %75, %76, %77, %78, %79, %80, %81, %82, %83, %84, %85, %86, %87, %88, %89, %90, %91, %92, %93, %94, %95, %96, %97, %98, %99, %100, %101, %102, %103, %104, %105, %106, %107, %108, %109, %110, %111, %112, %113, %114, %115, %116, %117, %118, %119, %120, %121, %122, %123, %124, %125, %126, %127}, a, b, 0, 1, 1, 0, %130;\n}\n"
    : "=f"(d[R0 + 0]), "=f"(d[R0 + 1]), "=f"(d[R0 + 2]), "=f"(d[R0 + 3]), "=f"(d[R0 + 4]), "=f"(d[R0 + 5]), "=f"(d[R0 + 6]), "=f"(d[R0 + 7]), "=f"(d[R0 + 8]), "=f"(d[R0 + 9]), "=f"(d[R0 + 10]), "=f"(d[R0 + 11]), "=f"(d[R0 + 12]), "=f"(d[R0 + 13]), "=f"(d[R0 + 14]), "=f"(d[R0 + 15]), "=f"(d[R0 + 16]), "=f"(d[R0 + 17]), "=f"(d[R0 + 18]), "=f"(d[R0 + 19]), "=f"(d[R0 + 20]), "=f"(d[R0 + 21]), "=f"(d[R0 + 22]), "=f"(d[R0 + 23]), "=f"(d[R0 + 24]), "=f"(d[R0 + 25]), "=f"(d[R0 + 26]), "=f"(d[R0 + 27]), "=f"(d[R0 + 28]), "=f"(d[R0 + 29]), "=f"(d[R0 + 30]), "=f"(d[R0 + 31]), "=f"(d[R0 + 32]), "=f"(d[R0 + 33]), "=f"(d[R0 + 34]), "=f"(d[R0 + 35]), "=f"(d[R0 + 36]), "=f"(d[R0 + 37]), "=f"(d[R0 + 38]), "=f"(d[R0 + 39]), "=f"(d[R0 + 40]), "=f"(d[R0 + 41]), "=f"(d[R0 + 42]), "=f"(d[R0 + 43]), "=f"(d[R0 + 44]), "=f"(d[R0 + 45]), "=f"(d[R0 + 46]), "=f"(d[R0 + 47]), "=f"(d[R0 + 48]), "=f"(d[R0 + 49]), "=f"(d[R0 + 50]), "=f"(d[R0 + 51]), "=f"(d[R0 + 52]), "=f"(d[R0 + 53]), "=f"(d[R0 + 54]), "=f"(d[R0 + 55]), "=f"(d[R0 + 56]), "=f"(d[R0 + 57]), "=f"(d[R0 + 58]), "=f"(d[R0 + 59]), "=f"(d[R0 + 60]), "=f"(d[R0 + 61]), "=f"(d[R0 + 62]), "=f"(d[R0 + 63]), "=f"(d[R0 + 64]), "=f"(d[R0 + 65]), "=f"(d[R0 + 66]), "=f"(d[R0 + 67]), "=f"(d[R0 + 68]), "=f"(d[R0 + 69]), "=f"(d[R0 + 70]), "=f"(d[R0 + 71]), "=f"(d[R0 + 72]), "=f"(d[R0 + 73]), "=f"(d[R0 + 74]), "=f"(d[R0 + 75]), "=f"(d[R0 + 76]), "=f"(d[R0 + 77]), "=f"(d[R0 + 78]), "=f"(d[R0 + 79]), "=f"(d[R0 + 80]), "=f"(d[R0 + 81]), "=f"(d[R0 + 82]), "=f"(d[R0 + 83]), "=f"(d[R0 + 84]), "=f"(d[R0 + 85]), "=f"(d[R0 + 86]), "=f"(d[R0 + 87]), "=f"(d[R0 + 88]), "=f"(d[R0 + 89]), "=f"(d[R0 + 90]), "=f"(d[R0 + 91]), "=f"(d[R0 + 92]), "=f"(d[R0 + 93]), "=f"(d[R0 + 94]), "=f"(d[R0 + 95]), "=f"(d[R0 + 96]), "=f"(d[R0 + 97]), "=f"(d[R0 + 98]), "=f"(d[R0 + 99]), "=f"(d[R0 + 100]), "=f"(d[R0 + 101]), "=f"(d[R0 + 102]), "=f"(d[R0 + 103]), "=f"(d[R0 + 104]), "=f"(d[R0 + 105]), "=f"(d[R0 + 106]), "=f"(d[R0 + 107]), "=f"(d[R0 + 108]), "=f"(d[R0 + 109]), "=f"(d[R0 + 110]), "=f"(d[R0 + 111]), "=f"(d[R0 + 112]), "=f"(d[R0 + 113]), "=f"(d[R0 + 114]), "=f"(d[R0 + 115]), "=f"(d[R0 + 116]), "=f"(d[R0 + 117]), "=f"(d[R0 + 118]), "=f"(d[R0 + 119]), "=f"(d[R0 + 120]), "=f"(d[R0 + 121]), "=f"(d[R0 + 122]), "=f"(d[R0 + 123]), "=f"(d[R0 + 124]), "=f"(d[R0 + 125]), "=f"(d[R0 + 126]), "=f"(d[R0 + 127])
    : "l"(da), "l"(db), "n"(TB), "n"(OA), "n"(OB));
}
template <int TB, int OA, int OB, int R0 = 0, int NA> __device__ __forceinline__ void wgmma_ss1_n128(float (&d)[NA], uint64_t da, uint64_t db) {
  asm volatile("{\n.reg .b64 a, b;\nadd.s64 a, %64, %67;\nadd.s64 b, %65, %68;\n"
    "wgmma.mma_async.sync.aligned.m64n128k16.f32.bf16.bf16 "
    "{%0, %1, %2, %3, %4, %5, %6, %7, %8, %9, %10, %11, %12, %13, %14, %15, %16, %17, %18, %19, %20, %21, %22, %23, %24, %25, %26, %27, %28, %29, %30, %31, %32, %33, %34, %35, %36, %37, %38, %39, %40, %41, %42, %43, %44, %45, %46, %47, %48, %49, %50, %51, %52, %53, %54, %55, %56, %57, %58, %59, %60, %61, %62, %63}, a, b, 1, 1, 1, 0, %66;\n}\n"
    : "+f"(d[R0 + 0]), "+f"(d[R0 + 1]), "+f"(d[R0 + 2]), "+f"(d[R0 + 3]), "+f"(d[R0 + 4]), "+f"(d[R0 + 5]), "+f"(d[R0 + 6]), "+f"(d[R0 + 7]), "+f"(d[R0 + 8]), "+f"(d[R0 + 9]), "+f"(d[R0 + 10]), "+f"(d[R0 + 11]), "+f"(d[R0 + 12]), "+f"(d[R0 + 13]), "+f"(d[R0 + 14]), "+f"(d[R0 + 15]), "+f"(d[R0 + 16]), "+f"(d[R0 + 17]), "+f"(d[R0 + 18]), "+f"(d[R0 + 19]), "+f"(d[R0 + 20]), "+f"(d[R0 + 21]), "+f"(d[R0 + 22]), "+f"(d[R0 + 23]), "+f"(d[R0 + 24]), "+f"(d[R0 + 25]), "+f"(d[R0 + 26]), "+f"(d[R0 + 27]), "+f"(d[R0 + 28]), "+f"(d[R0 + 29]), "+f"(d[R0 + 30]), "+f"(d[R0 + 31]), "+f"(d[R0 + 32]), "+f"(d[R0 + 33]), "+f"(d[R0 + 34]), "+f"(d[R0 + 35]), "+f"(d[R0 + 36]), "+f"(d[R0 + 37]), "+f"(d[R0 + 38]), "+f"(d[R0 + 39]), "+f"(d[R0 + 40]), "+f"(d[R0 + 41]), "+f"(d[R0 + 42]), "+f"(d[R0 + 43]), "+f"(d[R0 + 44]), "+f"(d[R0 + 45]), "+f"(d[R0 + 46]), "+f"(d[R0 + 47]), "+f"(d[R0 + 48]), "+f"(d[R0 + 49]), "+f"(d[R0 + 50]), "+f"(d[R0 + 51]), "+f"(d[R0 + 52]), "+f"(d[R0 + 53]), "+f"(d[R0 + 54]), "+f"(d[R0 + 55]), "+f"(d[R0 + 56]), "+f"(d[R0 + 57]), "+f"(d[R0 + 58]), "+f"(d[R0 + 59]), "+f"(d[R0 + 60]), "+f"(d[R0 + 61]), "+f"(d[R0 + 62]), "+f"(d[R0 + 63])
    : "l"(da), "l"(db), "n"(TB), "n"(OA), "n"(OB));
}
template <int TB, int OA, int OB, int R0 = 0, int NA> __device__ __forceinline__ void wgmma_ss1_n144(float (&d)[NA], uint64_t da, uint64_t db) {
  asm volatile("{\n.reg .b64 a, b;\nadd.s64 a, %72, %75;\nadd.s64 b, %73, %76;\n"
    "wgmma.mma_async.sync.aligned.m64n144k16.f32.bf16.bf16 "
    "{%0, %1, %2, %3, %4, %5, %6, %7, %8, %9, %10, %11, %12, %13, %14, %15, %16, %17, %18, %19, %20, %21, %22, %23, %24, %25, %26, %27, %28, %29, %30, %31, %32, %33, %34, %35, %36, %37, %38, %39, %40, %41, %42, %43, %44, %45, %46, %47, %48, %49, %50, %51, %52, %53, %54, %55, %56, %57, %58, %59, %60, %61, %62, %63, %64, %65, %66, %67, %68, %69, %70, %71}, a, b, 1, 1, 1, 0, %74;\n}\n"
    : "+f"(d[R0 + 0]), "+f"(d[R0 + 1]), "+f"(d[R0 + 2]), "+f"(d[R0 + 3]), "+f"(d[R0 + 4]), "+f"(d[R0 + 5]), "+f"(d[R0 + 6]), "+f"(d[R0 + 7]), "+f"(d[R0 + 8]), "+f"(d[R0 + 9]), "+f"(d[R0 + 10]), "+f"(d[R0 + 11]), "+f"(d[R0 + 12]), "+f"(d[R0 + 13]), "+f"(d[R0 + 14]), "+f"(d[R0 + 15]), "+f"(d[R0 + 16]), "+f"(d[R0 + 17]), "+f"(d[R0 + 18]), "+f"(d[R0 + 19]), "+f"(d[R0 + 20]), "+f"(d[R0 + 21]), "+f"(d[R0 + 22]), "+f"(d[R0 + 23]), "+f"(d[R0 + 24]), "+f"(d[R0 + 25]), "+f"(d[R0 + 26]), "+f"(d[R0 + 27]), "+f"(d[R0 + 28]), "+f"(d[R0 + 29]), "+f"(d[R0 + 30]), "+f"(d[R0 + 31]), "+f"(d[R0 + 32]), "+f"(d[R0 + 33]), "+f"(d[R0 + 34]), "+f"(d[R0 + 35]), "+f"(d[R0 + 36]), "+f"(d[R0 + 37]), "+f"(d[R0 + 38]), "+f"(d[R0 + 39]), "+f"(d[R0 + 40]), "+f"(d[R0 + 41]), "+f"(d[R0 + 42]), "+f"(d[R0 + 43]), "+f"(d[R0 + 44]), "+f"(d[R0 + 45]), "+f"(d[R0 + 46]), "+f"(d[R0 + 47]), "+f"(d[R0 + 48]), "+f"(d[R0 + 49]), "+f"(d[R0 + 50]), "+f"(d[R0 + 51]), "+f"(d[R0 + 52]), "+f"(d[R0 + 53]), "+f"(d[R0 + 54]), "+f"(d[R0 + 55]), "+f"(d[R0 + 56]), "+f"(d[R0 + 57]), "+f"(d[R0 + 58]), "+f"(d[R0 + 59]), "+f"(d[R0 + 60]), "+f"(d[R0 + 61]), "+f"(d[R0 + 62]), "+f"(d[R0 + 63]), "+f"(d[R0 + 64]), "+f"(d[R0 + 65]), "+f"(d[R0 + 66]), "+f"(d[R0 + 67]), "+f"(d[R0 + 68]), "+f"(d[R0 + 69]), "+f"(d[R0 + 70]), "+f"(d[R0 + 71])
    : "l"(da), "l"(db), "n"(TB), "n"(OA), "n"(OB));
}
template <int TB, int OA, int OB, int R0 = 0, int NA> __device__ __forceinline__ void wgmma_ss1_n192(float (&d)[NA], uint64_t da, uint64_t db) {
  asm volatile("{\n.reg .b64 a, b;\nadd.s64 a, %96, %99;\nadd.s64 b, %97, %100;\n"
    "wgmma.mma_async.sync.aligned.m64n192k16.f32.bf16.bf16 "
    "{%0, %1, %2, %3, %4, %5, %6, %7, %8, %9, %10, %11, %12, %13, %14, %15, %16, %17, %18, %19, %20, %21, %22, %23, %24, %25, %26, %27, %28, %29, %30, %31, %32, %33, %34, %35, %36, %37, %38, %39, %40, %41, %42, %43, %44, %45, %46, %47, %48, %49, %50, %51, %52, %53, %54, %55, %56, %57, %58, %59, %60, %61, %62, %63, %64, %65, %66, %67, %68, %69, %70, %71, %72, %73, %74, %75, %76, %77, %78, %79, %80, %81, %82, %83, %84, %85, %86, %87, %88, %89, %90, %91, %92, %93, %94, %95}, a, b, 1, 1, 1, 0, %98;\n}\n"
    : "+f"(d[R0 + 0]), "+f"(d[R0 + 1]), "+f"(d[R0 + 2]), "+f"(d[R0 + 3]), "+f"(d[R0 + 4]), "+f"(d[R0 + 5]), "+f"(d[R0 + 6]), "+f"(d[R0 + 7]), "+f"(d[R0 + 8]), "+f"(d[R0 + 9]), "+f"(d[R0 + 10]), "+f"(d[R0 + 11]), "+f"(d[R0 + 12]), "+f"(d[R0 + 13]), "+f"(d[R0 + 14]), "+f"(d[R0 + 15]), "+f"(d[R0 + 16]), "+f"(d[R0 + 17]), "+f"(d[R0 + 18]), "+f"(d[R0 + 19]), "+f"(d[R0 + 20]), "+f"(d[R0 + 21]), "+f"(d[R0 + 22]), "+f"(d[R0 + 23]), "+f"(d[R0 + 24]), "+f"(d[R0 + 25]), "+f"(d[R0 + 26]), "+f"(d[R0 + 27]), "+f"(d[R0 + 28]), "+f"(d[R0 + 29]), "+f"(d[R0 + 30]), "+f"(d[R0 + 31]), "+f"(d[R0 + 32]), "+f"(d[R0 + 33]), "+f"(d[R0 + 34]), "+f"(d[R0 + 35]), "+f"(d[R0 + 36]), "+f"(d[R0 + 37]), "+f"(d[R0 + 38]), "+f"(d[R0 + 39]), "+f"(d[R0 + 40]), "+f"(d[R0 + 41]), "+f"(d[R0 + 42]), "+f"(d[R0 + 43]), "+f"(d[R0 + 44]), "+f"(d[R0 + 45]), "+f"(d[R0 + 46]), "+f"(d[R0 + 47]), "+f"(d[R0 + 48]), "+f"(d[R0 + 49]), "+f"(d[R0 + 50]), "+f"(d[R0 + 51]), "+f"(d[R0 + 52]), "+f"(d[R0 + 53]), "+f"(d[R0 + 54]), "+f"(d[R0 + 55]), "+f"(d[R0 + 56]), "+f"(d[R0 + 57]), "+f"(d[R0 + 58]), "+f"(d[R0 + 59]), "+f"(d[R0 + 60]), "+f"(d[R0 + 61]), "+f"(d[R0 + 62]), "+f"(d[R0 + 63]), "+f"(d[R0 + 64]), "+f"(d[R0 + 65]), "+f"(d[R0 + 66]), "+f"(d[R0 + 67]), "+f"(d[R0 + 68]), "+f"(d[R0 + 69]), "+f"(d[R0 + 70]), "+f"(d[R0 + 71]), "+f"(d[R0 + 72]), "+f"(d[R0 + 73]), "+f"(d[R0 + 74]), "+f"(d[R0 + 75]), "+f"(d[R0 + 76]), "+f"(d[R0 + 77]), "+f"(d[R0 + 78]), "+f"(d[R0 + 79]), "+f"(d[R0 + 80]), "+f"(d[R0 + 81]), "+f"(d[R0 + 82]), "+f"(d[R0 + 83]), "+f"(d[R0 + 84]), "+f"(d[R0 + 85]), "+f"(d[R0 + 86]), "+f"(d[R0 + 87]), "+f"(d[R0 + 88]), "+f"(d[R0 + 89]), "+f"(d[R0 + 90]), "+f"(d[R0 + 91]), "+f"(d[R0 + 92]), "+f"(d[R0 + 93]), "+f"(d[R0 + 94]), "+f"(d[R0 + 95])
    : "l"(da), "l"(db), "n"(TB), "n"(OA), "n"(OB));
}
template <int TB, int OA, int OB, int R0 = 0, int NA> __device__ __forceinline__ void wgmma_ss1_n24(float (&d)[NA], uint64_t da, uint64_t db) {
  asm volatile("{\n.reg .b64 a, b;\nadd.s64 a, %12, %15;\nadd.s64 b, %13, %16;\n"
    "wgmma.mma_async.sync.aligned.m64n24k16.f32.bf16.bf16 "
    "{%0, %1, %2, %3, %4, %5, %6, %7, %8, %9, %10, %11}, a, b, 1, 1, 1, 0, %14;\n}\n"
    : "+f"(d[R0 + 0]), "+f"(d[R0 + 1]), "+f"(d[R0 + 2]), "+f"(d[R0 + 3]), "+f"(d[R0 + 4]), "+f"(d[R0 + 5]), "+f"(d[R0 + 6]), "+f"(d[R0 + 7]), "+f"(d[R0 + 8]), "+f"(d[R0 + 9]), "+f"(d[R0 + 10]), "+f"(d[R0 + 11])
    : "l"(da), "l"(db), "n"(TB), "n"(OA), "n"(OB));
}
template <int TB, int OA, int OB, int R0 = 0, int NA> __device__ __forceinline__ void wgmma_ss1_n256(float (&d)[NA], uint64_t da, uint64_t db) {
  asm volatile("{\n.reg .b64 a, b;\nadd.s64 a, %128, %131;\nadd.s64 b, %129, %132;\n"
    "wgmma.mma_async.sync.aligned.m64n256k16.f32.bf16.bf16 "
    "{%0, %1, %2, %3, %4, %5, %6, %7, %8, %9, %10, %11, %12, %13, %14, %15, %16, %17, %18, %19, %20, %21, %22, %23, %24, %25, %26, %27, %28, %29, %30, %31, %32, %33, %34, %35, %36, %37, %38, %39, %40, %41, %42, %43, %44, %45, %46, %47, %48, %49, %50, %51, %52, %53, %54, %55, %56, %57, %58, %59, %60, %61, %62, %63, %64, %65, %66, %67, %68, %69, %70, %71, %72, %73, %74, %75, %76, %77, %78, %79, %80, %81, %82, %83, %84, %85, %86, %87, %88, %89, %90, %91, %92, %93, %94, %95, %96, %97, %98, %99, %100, %101, %102, %103, %104, %105, %106, %107, %108, %109, %110, %111, %112, %113, %114, %115, %116, %117, %118, %119, %120, %121, %122, %123, %124, %125, %126, %127}, a, b, 1, 1, 1, 0, %130;\n}\n"
    : "+f"(d[R0 + 0]), "+f"(d[R0 + 1]), "+f"(d[R0 + 2]), "+f"(d[R0 + 3]), "+f"(d[R0 + 4]), "+f"(d[R0 + 5]), "+f"(d[R0 + 6]), "+f"(d[R0 + 7]), "+f"(d[R0 + 8]), "+f"(d[R0 + 9]), "+f"(d[R0 + 10]), "+f"(d[R0 + 11]), "+f"(d[R0 + 12]), "+f"(d[R0 + 13]), "+f"(d[R0 + 14]), "+f"(d[R0 + 15]), "+f"(d[R0 + 16]), "+f"(d[R0 + 17]), "+f"(d[R0 + 18]), "+f"(d[R0 + 19]), "+f"(d[R0 + 20]), "+f"(d[R0 + 21]), "+f"(d[R0 + 22]), "+f"(d[R0 + 23]), "+f"(d[R0 + 24]), "+f"(d[R0 + 25]), "+f"(d[R0 + 26]), "+f"(d[R0 + 27]), "+f"(d[R0 + 28]), "+f"(d[R0 + 29]), "+f"(d[R0 + 30]), "+f"(d[R0 + 31]), "+f"(d[R0 + 32]), "+f"(d[R0 + 33]), "+f"(d[R0 + 34]), "+f"(d[R0 + 35]), "+f"(d[R0 + 36]), "+f"(d[R0 + 37]), "+f"(d[R0 + 38]), "+f"(d[R0 + 39]), "+f"(d[R0 + 40]), "+f"(d[R0 + 41]), "+f"(d[R0 + 42]), "+f"(d[R0 + 43]), "+f"(d[R0 + 44]), "+f"(d[R0 + 45]), "+f"(d[R0 + 46]), "+f"(d[R0 + 47]), "+f"(d[R0 + 48]), "+f"(d[R0 + 49]), "+f"(d[R0 + 50]), "+f"(d[R0 + 51]), "+f"(d[R0 + 52]), "+f"(d[R0 + 53]), "+f"(d[R0 + 54]), "+f"(d[R0 + 55]), "+f"(d[R0 + 56]), "+f"(d[R0 + 57]), "+f"(d[R0 + 58]), "+f"(d[R0 + 59]), "+f"(d[R0 + 60]), "+f"(d[R0 + 61]), "+f"(d[R0 + 62]), "+f"(d[R0 + 63]), "+f"(d[R0 + 64]), "+f"(d[R0 + 65]), "+f"(d[R0 + 66]), "+f"(d[R0 + 67]), "+f"(d[R0 + 68]), "+f"(d[R0 + 69]), "+f"(d[R0 + 70]), "+f"(d[R0 + 71]), "+f"(d[R0 + 72]), "+f"(d[R0 + 73]), "+f"(d[R0 + 74]), "+f"(d[R0 + 75]), "+f"(d[R0 + 76]), "+f"(d[R0 + 77]), "+f"(d[R0 + 78]), "+f"(d[R0 + 79]), "+f"(d[R0 + 80]), "+f"(d[R0 + 81]), "+f"(d[R0 + 82]), "+f"(d[R0 + 83]), "+f"(d[R0 + 84]), "+f"(d[R0 + 85]), "+f"(d[R0 + 86]), "+f"(d[R0 + 87]), "+f"(d[R0 + 88]), "+f"(d[R0 + 89]), "+f"(d[R0 + 90]), "+f"(d[R0 + 91]), "+f"(d[R0 + 92]), "+f"(d[R0 + 93]), "+f"(d[R0 + 94]), "+f"(d[R0 + 95]), "+f"(d[R0 + 96]), "+f"(d[R0 + 97]), "+f"(d[R0 + 98]), "+f"(d[R0 + 99]), "+f"(d[R0 + 100]), "+f"(d[R0 + 101]), "+f"(d[R0 + 102]), "+f"(d[R0 + 103]), "+f"(d[R0 + 104]), "+f"(d[R0 + 105]), "+f"(d[R0 + 106]), "+f"(d[R0 + 107]), "+f"(d[R0 + 108]), "+f"(d[R0 + 109]), "+f"(d[R0 + 110]), "+f"(d[R0 + 111]), "+f"(d[R0 + 112]), "+f"(d[R0 + 113]), "+f"(d[R0 + 114]), "+f"(d[R0 + 115]), "+f"(d[R0 + 116]), "+f"(d[R0 + 117]), "+f"(d[R0 + 118]), "+f"(d[R0 + 119]), "+f"(d[R0 + 120]), "+f"(d[R0 + 121]), "+f"(d[R0 + 122]), "+f"(d[R0 + 123]), "+f"(d[R0 + 124]), "+f"(d[R0 + 125]), "+f"(d[R0 + 126]), "+f"(d[R0 + 127])
    : "l"(da), "l"(db), "n"(TB), "n"(OA), "n"(OB));
}

constexpr int NMAIN = 128, NCTA = 132, NTHREADS = 384;
constexpr uint32_t SM_X = 0;
constexpr uint32_t SM_W = 147456;
constexpr uint32_t SM_KV = 196608;
constexpr uint32_t SM_BAR = 227328;
constexpr uint32_t SM_MISC = SM_BAR + 496, SM_G = SM_BAR + 512;
constexpr uint32_t SM_TOTAL = 228864;
constexpr uint32_t SM_AR = SM_W + 5 * 12288;
constexpr uint32_t SM_AO = 184320;
constexpr uint32_t W_SLOT = 16384, KV_SLOT = 5120, F2_SLOT = 30720;
constexpr int NRING = 6;
enum { B_AEMPTY = 0, B_AFULL = 5, B_GO = 10, B_GATE = 11,
       B_DONE = 12, B_IMG = 18, B_IMG2 = 19, B_Q = 20, B_PDONE = 21, B_T = 22,
       B_PF = 23,
       B_FULL = 24, B_HOK = 30, B_POK = 31, B_PFULL = 32,
       B_PEMPTY = 34, B_HDONE = 36, B_ODONE = 41 };
constexpr int NPLANE = 648;

struct Flags {
  unsigned launch[160];
  unsigned kv0[8 * 32], kv1[8 * 32];
  unsigned kq[8 * 32], ao[8 * 32];
  unsigned g[32];
  unsigned h[128 * 8];
  unsigned o[64 * 8];
  unsigned p[128 * 8];
};
__device__ __align__(128) Flags g_flags;
__device__ unsigned g_launch_aux[4];
__device__ __align__(1024) uint8_t g_kv[32 * 32 * KV_SLOT];
__device__ __align__(1024) uint8_t g_a2[16 * NPLANE * 2048];
__device__ __align__(1024) uint2 g_qs[NMAIN * 12 * 256];
__device__ __align__(1024) uint4 g_part[128 * 9 * 128];
__device__ __align__(1024) float4 g_ao[NMAIN * 3 * 256];
__device__ __align__(1024) float2 g_gate[2048];

struct Maps { CUtensorMap x, qm, qr, wg, wu, wgh, wuh, wdm, wdn, wom, won, out; };

__device__ __forceinline__ uint64_t mkdesc(uint32_t addr, uint32_t lbo, uint32_t sbo, uint32_t sw) {
  return (uint64_t)((addr & 0x3FFFF) >> 4) | ((uint64_t)(lbo >> 4) << 16) | ((uint64_t)(sbo >> 4) << 32) | ((uint64_t)sw << 62);
}
#define WG_FENCE() asm volatile("wgmma.fence.sync.aligned;" ::: "memory")
#define WG_COMMIT() asm volatile("wgmma.commit_group.sync.aligned;" ::: "memory")
#define WG_WAIT(n) asm volatile("wgmma.wait_group.sync.aligned " #n ";" ::: "memory")
template <int N> __device__ __forceinline__ void pin(float (&d)[N]) {
#pragma unroll
  for (int i = 0; i < N; i++) asm volatile("" : "+f"(d[i])::"memory");
}
template <int N> __device__ __forceinline__ void pin(uint32_t (&d)[N]) {
#pragma unroll
  for (int i = 0; i < N; i++) asm volatile("" : "+r"(d[i])::"memory");
}
__device__ __forceinline__ void mbar_wait(uint32_t bar, uint32_t parity) {
  asm volatile("{\n.reg .pred p;\nLW:\nmbarrier.try_wait.parity.shared::cta.b64 p, [%0], %1;\n@!p bra.uni LW;\n}\n" ::"r"(bar), "r"(parity) : "memory");
}
__device__ __forceinline__ void mbar_wait_early(uint32_t bar, uint32_t parity) {
  asm volatile("{\n.reg .pred p;\n.reg .u32 c;\nmbarrier.test_wait.parity.shared::cta.b64 p, [%0], %1;\n@p bra.uni LD;\nmov.u32 c, 0;\n"
               "LW:\nmbarrier.try_wait.parity.shared::cta.b64 p, [%0], %1;\n@p bra.uni LD;\n"
               "add.u32 c, c, 1;\nsetp.lt.u32 p, c, 100000000;\n@p bra.uni LW;\ntrap;\nLD:\n}\n" ::"r"(bar), "r"(parity) : "memory");
}
__device__ __forceinline__ void mbar_wait_long(uint32_t bar, uint32_t parity) {
  asm volatile("{\n.reg .pred p;\nLW:\nmbarrier.try_wait.parity.shared::cta.b64 p, [%0], %1, 100000;\n@!p bra.uni LW;\n}\n" ::"r"(bar), "r"(parity) : "memory");
}
__device__ __forceinline__ void mbar_wait_watch(uint32_t bar, uint32_t parity) {
  asm volatile("{\n.reg .pred p;\n.reg .u32 c;\nmov.u32 c, 0;\n"
               "LW:\nmbarrier.try_wait.parity.shared::cta.b64 p, [%0], %1, 100000;\n@p bra.uni LD;\n"
               "add.u32 c, c, 1;\nsetp.lt.u32 p, c, 40000;\n@p bra.uni LW;\ntrap;\nLD:\n}\n" ::"r"(bar), "r"(parity) : "memory");
}
#define ELECT "{\n.reg .pred p;\nelect.sync _|p, 0xffffffff;\n"
#define EXPECT "@p mbarrier.arrive.expect_tx.shared::cta.b64 _, [%0], %1;\n"
#define BULK "@p cp.async.bulk.shared::cluster.global.mbarrier::complete_tx::bytes "
#define TMA(d) "@p cp.async.bulk.tensor." d ".shared::cluster.global.mbarrier::complete_tx::bytes "
__device__ __forceinline__ void warp_init(uint32_t bar, uint32_t cnt) {
  asm volatile(ELECT "@p mbarrier.init.shared::cta.b64 [%0], %1;\n}\n" ::"r"(bar), "r"(cnt) : "memory");
}
__device__ __forceinline__ void warp_arrive(uint32_t bar) {
  asm volatile(ELECT "@p mbarrier.arrive.shared::cta.b64 _, [%0];\n}\n" ::"r"(bar) : "memory");
}
__device__ __forceinline__ void warp_arrive2(uint32_t bar) {
  asm volatile(ELECT "@p mbarrier.arrive.shared::cta.b64 _, [%0], 2;\n}\n" ::"r"(bar) : "memory");
}
__device__ __forceinline__ void ld_bulk(uint32_t bar, uint32_t bytes, uint32_t dst, const void* src) {
  asm volatile(ELECT EXPECT BULK "[%2], [%3], %1, [%0];\n}" ::"r"(bar), "r"(bytes), "r"(dst), "l"(src) : "memory");
}
__device__ __forceinline__ void ld_2d_only(uint32_t bar, uint32_t dst, const CUtensorMap* m, int c0, int c1) {
  asm volatile(ELECT TMA("2d") "[%1], [%2, {%3, %4}], [%0];\n}" ::"r"(bar), "r"(dst), "l"(m), "r"(c0), "r"(c1) : "memory");
}
#define TMA_MC(d) "@p cp.async.bulk.tensor." d ".shared::cluster.global.mbarrier::complete_tx::bytes.multicast::cluster "
__device__ __forceinline__ void ld_2d_mc(uint32_t bar, uint32_t bytes, uint32_t dst, const CUtensorMap* m, int c0, int c1) {
  asm volatile(ELECT EXPECT TMA_MC("2d") "[%2], [%3, {%4, %5}], [%0], %6;\n}"
               ::"r"(bar), "r"(bytes), "r"(dst), "l"(m), "r"(c0), "r"(c1), "h"((uint16_t)3) : "memory");
}
__device__ __forceinline__ void ld_3d_mc(uint32_t bar, uint32_t bytes, uint32_t dst, const CUtensorMap* m, int c0, int c1) {
  asm volatile(ELECT EXPECT TMA_MC("3d") "[%2], [%3, {%4, %5, 0}], [%0], %6;\n}"
               ::"r"(bar), "r"(bytes), "r"(dst), "l"(m), "r"(c0), "r"(c1), "h"((uint16_t)3) : "memory");
}
__device__ __forceinline__ void ld_kv_mc(uint32_t bar, uint32_t dst, const void* src) {
  asm volatile(ELECT EXPECT "@p cp.async.bulk.shared::cluster.global.mbarrier::complete_tx::bytes.multicast::cluster [%2], [%3], 5120, [%0], %4;\n}"
               ::"r"(bar), "r"(2 * KV_SLOT), "r"(dst), "l"(src), "h"((uint16_t)3) : "memory");
}
__device__ __forceinline__ uint32_t peer_addr(uint32_t a, int peer) { uint32_t r; asm("mapa.shared::cluster.u32 %0, %1, %2;" : "=r"(r) : "r"(a), "r"(peer)); return r; }
__device__ __forceinline__ void warp_arrive_both(uint32_t bar, uint32_t rbar) {
  asm volatile(ELECT "@p mbarrier.arrive.shared::cta.b64 _, [%0];\n@p mbarrier.arrive.shared::cluster.b64 _, [%1];\n}\n" ::"r"(bar), "r"(rbar) : "memory");
}
__device__ __forceinline__ void pf_2d(const CUtensorMap* m, int c0, int c1) {
  asm volatile(ELECT "@p cp.async.bulk.prefetch.tensor.2d.L2.global [%0, {%1, %2}];\n}" ::"l"(m), "r"(c0), "r"(c1) : "memory");
}
__device__ __forceinline__ void pf_bulk(const void* src, uint32_t bytes) {
  asm volatile(ELECT "@p cp.async.bulk.prefetch.L2.global [%0], %1;\n}" ::"l"(src), "r"(bytes) : "memory");
}
__device__ __forceinline__ void st_bulk(void* dst, uint32_t src, uint32_t bytes) {
  asm volatile(ELECT "@p cp.async.bulk.global.shared::cta.bulk_group [%0], [%1], %2;\n@p cp.async.bulk.commit_group;\n}" ::"l"(dst), "r"(src), "r"(bytes) : "memory");
}
#define ST_WAIT(what) asm volatile(ELECT "@p cp.async.bulk.wait_group" what ";\n}" ::: "memory")
__device__ __forceinline__ void flag_add(unsigned* f) {
  asm volatile(ELECT "@p red.release.gpu.global.add.u32 [%0], 1;\n}" ::"l"(f) : "memory");
}
__device__ __forceinline__ void flag_add_relaxed(unsigned* f) {
  asm volatile(ELECT "@p red.relaxed.gpu.global.add.u32 [%0], 1;\n}" ::"l"(f) : "memory");
}
__device__ __forceinline__ void fence_async_global() { asm volatile("fence.proxy.async.global;" ::: "memory"); }
__device__ __forceinline__ void fence_async_smem() { asm volatile("fence.proxy.async.shared::cta;" ::: "memory"); }
__device__ __forceinline__ unsigned flags_wait(const unsigned* f, unsigned target) {
  unsigned tag;
  asm volatile("{\n.reg .pred p;\n.reg .u32 c;\n.reg .s32 v;\n.reg .b64 w;\nmov.u32 c, 0;\n"
               "LW:\nld.acquire.gpu.global.b64 w, [%1];\nmov.b64 {v, %0}, w;\nsub.s32 v, v, %2;\nsetp.ge.s32 p, v, 0;\n"
               "vote.sync.all.pred p, p, 0xffffffff;\n@p bra.uni LD;\n"
               "add.u32 c, c, 1;\nsetp.lt.u32 p, c, 4000000;\n@p bra.uni LW;\ntrap;\nLD:\n}\n" : "=r"(tag) : "l"(f), "r"(target) : "memory");
  return tag;
}
__device__ __forceinline__ float ex2(float x) { float y; asm volatile("ex2.approx.ftz.f32 %0, %1;" : "=f"(y) : "f"(x)); return y; }
__device__ __forceinline__ float ex2n(float x) { float y; asm volatile("ex2.approx.ftz.f32 %0, %1; // b" : "=f"(y) : "f"(x)); return y; }
__device__ __forceinline__ float tanh_fast(float x) { float y; asm("tanh.approx.f32 %0, %1;" : "=f"(y) : "f"(x)); return y; }
__device__ __forceinline__ float rcp_fast(float x) { float y; asm("rcp.approx.ftz.f32 %0, %1;" : "=f"(y) : "f"(x)); return y; }
__device__ __forceinline__ float max_nan(float a, float b) { float y; asm("max.NaN.f32 %0, %1, %2;" : "=f"(y) : "f"(a), "f"(b)); return y; }
__device__ __forceinline__ uint32_t pack2(float lo, float hi) { uint32_t r; asm("cvt.rn.bf16x2.f32 %0, %1, %2;" : "=r"(r) : "f"(hi), "f"(lo)); return r; }
__device__ __forceinline__ void sts32(uint32_t a, uint32_t v) { asm volatile("st.shared.u32 [%0], %1;" ::"r"(a), "r"(v) : "memory"); }
__device__ __forceinline__ uint32_t lds32(uint32_t a) { uint32_t v; asm volatile("ld.shared.u32 %0, [%1];" : "=r"(v) : "r"(a) : "memory"); return v; }
__device__ __forceinline__ void stg32(void* p, uint32_t v) { asm volatile("st.global.u32 [%0], %1;" ::"l"(p), "r"(v) : "memory"); }
__device__ __forceinline__ void stsm4(uint32_t a, uint32_t r0, uint32_t r1, uint32_t r2, uint32_t r3) {
  asm volatile("stmatrix.sync.aligned.m8n8.x4.shared.b16 [%0], {%1, %2, %3, %4};" ::"r"(a), "r"(r0), "r"(r1), "r"(r2), "r"(r3) : "memory");
}
__device__ __forceinline__ float bf_lo(uint32_t v) { return __uint_as_float(v << 16); }
__device__ __forceinline__ float bf_hi(uint32_t v) { return __uint_as_float(v & 0xFFFF0000u); }
__device__ __forceinline__ int tid_now() { int v; asm volatile("mov.u32 %0, %%tid.x;" : "=r"(v)); return v; }

__device__ __forceinline__ unsigned launch_number() {
  unsigned v;
  asm volatile("ld.relaxed.gpu.global.u32 %0, [%1];" : "=r"(v) : "l"(&g_flags.launch[blockIdx.x]) : "memory");
  return v;
}
__device__ __forceinline__ void producer_w(const Maps& mp, const uint8_t* wqkv, uint32_t sb, int rb, int s, int r) {
  const uint32_t bar = sb + SM_BAR, wb = sb + SM_W;
  {
    int slot = 2, ph = 1;
#pragma unroll 1
    for (int st = 0; st < 18; st++) {
      const uint32_t fb = bar + 8 * (B_AFULL + slot);
      const bool xk = r && !(st & 1);
      if (st >= 5) mbar_wait_long(bar + 8 * (B_AEMPTY + slot), ph);
      if (xk && st > 0) ld_2d_only(fb, sb + SM_X + st * 8192, &mp.x, st * 32, rb * 128);
      ld_3d_mc(fb, r ? (xk ? 17920 : 1536) : 12288, (r ? sb + SM_AR : wb) + (2 * slot + (rb & 1)) * (r ? 768 : 6144), &mp.qm + r, 72 * s + 64 * r, 32 * st + 16 * (rb & 1));
      if (0x48 >> st & 1) {
        const int late = st >> 2;
        if (!r) pf_bulk(wqkv + (160 + 208 * late) * 3456 + blockIdx.x * 5616, 5616);
        else if (s < 3) pf_2d(&mp.x, (3 + 3 * late + s) * 64, rb * 128);
      }
      if (st == 14 && !r) warp_arrive(bar + 8 * B_PF);
      if (++slot == 5) slot = 0;
      if (slot == 2) ph ^= 1;
    }
  }
  {
    int c0 = 576 * s + 64 * r, k0 = 0, dk = 32;
    const CUtensorMap* wm = &mp.wg + (rb & 1);
    uint32_t fb = bar + 8 * B_FULL, db = bar + 8 * (B_DONE + 3);
    mbar_wait_long(bar + 8 * (B_AEMPTY + 0), 0);
#pragma unroll 1
    for (int h = 0; h < 26 + r; h++) {
#pragma unroll
      for (int pos = 0; pos < 3; pos++) {
        mbar_wait_long(h ? db + 8 * pos : bar + 8 * (B_AEMPTY + 1 + pos), h ? ((h - 1) >> 1) & 1 : pos != 0);
        ld_2d_mc(fb + 8 * pos, 8192, wb + pos * W_SLOT + (rb & 1) * 8192 + r * 4096, wm, c0, k0);
        if (h == 26) ld_2d_mc(fb + 8 * pos, 8192, wb + pos * W_SLOT + (rb & 1) * 8192, wm, c0, k0 - 32);
        k0 += dk;
      }
      if (k0 == 576) { k0 = 0; c0 += 128; }
      if (h == 23) { c0 -= 64 * r; k0 = 32 * r; dk = 64; }
      const uint32_t t = (h & 1) ? -24 : 24;
      fb += t; db -= t;
    }
  }
  const int ch0 = (s & 4) * 12;
  int i = 3, ph = 0;
  uint32_t fdst = sb + SM_X;
  auto wait_slot = [&](int m) { mbar_wait_long(bar + 8 * (B_DONE + i + (m == 3 || m == 4)), ph); };
  auto adv = [&]() {
    fdst += F2_SLOT;
    if (++i == NRING) { i = 0; ph ^= 1; }
    if (i == 3) fdst = sb + SM_X;
  };
  if (r) {
    const int c0 = (s & 3) * 144;
#pragma unroll 1
    for (int m = 0; m < 60; m++) {
      wait_slot(m);
      const int c1 = m < 48 ? 0 : 6 * m - 288, c2 = m < 48 ? 8 * (ch0 + 12 * (m & 3) + (m >> 2)) : 0;
      const CUtensorMap* wm = m < 48 ? &mp.wdm : &mp.wom;
      asm volatile(ELECT EXPECT TMA_MC("3d") "[%2], [%3, {%6, %8, %9}], [%0], %11;\n" TMA_MC("3d") "[%4], [%5, {%7, %8, %10}], [%0], %11;\n}"
                   ::"r"(bar + 8 * (B_FULL + i)), "r"(13824), "r"(fdst + 12288 + 6144 * (rb & 1)), "l"(wm), "r"(fdst + 24576 + 3072 * (rb & 1)), "l"(wm + 1),
                     "r"(c0 + 64 * (rb & 1)), "r"(c0 + 128), "r"(c1), "r"(c2), "r"(c2 + 4 * (rb & 1)), "h"((uint16_t)3) : "memory");
      adv();
    }
  } else {
    const uint8_t* asrc = g_a2 + (size_t)rb * NPLANE * 2048;
    int gate = 0;
#pragma unroll 1
    for (int m = 0; m < 57; m++) {
      wait_slot(m);
      if (m == gate) {
        mbar_wait_long(bar + 8 * B_HOK, m == 20);
        fence_async_global();
        if (m == 48)
          asm volatile(ELECT "@p mbarrier.expect_tx.relaxed.cta.shared::cta.b64 [%0], 12288;\n" BULK "[%1], [%2], 12288, [%0];\n}"
                       ::"r"(bar + 8 * (B_FULL + i)), "r"(sb + SM_AO), "l"(g_ao + (rb * 8 + s) * 768) : "memory");
        gate = m == 0 ? 20 : 48;
      }
      ld_bulk(bar + 8 * (B_FULL + i), 12288, fdst, asrc + (m < 48 ? ch0 + 12 * (m & 3) + (m >> 2) : 48 + m) * 12288);
      adv();
    }
  }
}
__device__ __forceinline__ void producer_kv(const Maps& mp, const uint8_t* wd, const uint8_t* wo, uint32_t sb, int rb, int s) {
  const uint32_t bar = sb + SM_BAR;
  const unsigned epoch = launch_number();
  auto prefetch = [&](int it) {
    if (it <= 13) {
      const int ft = it / 3;
      if (rb < (ft < 4 ? 12 : 9)) pf_2d(&mp.wgh + ((ft < 4 ? rb : it) & 1), 576 * s + 128 * ft + (ft < 4 ? 32 * (rb & 2) : 0), ft < 4 ? 192 * (it - 3 * ft) + 64 * (rb >> 2) : 64 * rb);
    }
    if (it >= 13 && it < 20) {
      const int id = rb * 4 + (s & 3);
      pf_bulk(it < 19 ? wd + (size_t)(((s & 4) + (id >> 4)) * 12 + 2 * (it - 13)) * 55296 + (id & 15) * 6912 : wo + blockIdx.x * 5184, it < 19 ? 6912 : 5184);
    }
  };
  warp_arrive(bar + 8 * B_FULL); warp_arrive(bar + 8 * (B_FULL + 2)); warp_arrive(bar + 8 * (B_FULL + 4));
  const uint8_t* src = g_kv + (size_t)s * 128 * KV_SLOT;
  mbar_wait_long(bar + 8 * B_PF, 0);
  unsigned tag = 0;
  int fi = 0, ph = 0;
#pragma unroll 1
  for (int it = 0; it < 24; it++) {
    if (it == 3 || it == 8) {
      if (it == 3) mbar_wait_long(bar + 8 * B_IMG, 0);
      tag = flags_wait(it == 3 ? &g_flags.kv0[s * 32] : &g_flags.kv1[s * 32], epoch * 16 + 16);
      fence_async_global();
    }
    if (it >= 3) {
#pragma unroll 1
      do {
        const int di = fi == 4 ? 0 : fi + 2;
        if (di == 0) ph ^= 1;
        if (it == 3 && fi == 2) {
          const bool safe = __all_sync(0xffffffffu, tag != epoch + 1);
          sts32(sb + SM_MISC + 4, safe);
          warp_arrive(bar + 8 * B_GO);
          if (!safe) {
            flags_wait(&g_flags.kv1[s * 32], epoch * 16 + 16);
            fence_async_global();
#pragma unroll 1
            for (int n = 0; n < 128; n++) {
              mbar_wait_long(bar + 8 * (B_PEMPTY + (n & 1)), (n >> 1 & 1) ^ 1);
              ld_bulk(bar + 8 * (B_PFULL + (n & 1)), KV_SLOT, sb + SM_KV + (4 + (n & 1)) * KV_SLOT, src + (n - 2) * (int)KV_SLOT);
            }
          }
        }
        mbar_wait_long(bar + 8 * (B_DONE + di), ph);
        ld_kv_mc(bar + 8 * (B_FULL + fi), sb + SM_KV + (fi + (rb & 1)) * KV_SLOT, src + (rb & 1) * KV_SLOT);
        src += 2 * KV_SLOT;
        fi = di;
      } while (fi != 0);
    }
    prefetch(it);
  }
#pragma unroll 1
  for (int n = 132; n <= 140; n += 2) {
    mbar_wait_long(bar + 8 * (B_FULL + fi), n < 138);
    warp_arrive(bar + 8 * (B_FULL + fi));
    fi = fi == 4 ? 0 : fi + 2;
  }
  mbar_wait_long(bar + 8 * B_PDONE, 0);
  flag_add(&g_flags.p[((rb * 4 + (s & 3)) * 2 + 1 - (s >> 2)) * 8]);
  flags_wait(&g_flags.p[((rb * 4 + (s & 3)) * 2 + (s >> 2)) * 8], epoch + 1);
  warp_arrive(bar + 8 * B_POK);
}
__device__ __forceinline__ void publisher(const Maps& mp, uint32_t sb, int rb, int s, int lane) {
  const uint32_t bar = sb + SM_BAR;
  const unsigned epoch = launch_number();
  mbar_wait_watch(bar + 8 * B_IMG, 0);
  st_bulk(g_kv + (size_t)(s * 128 + rb * 2) * KV_SLOT, sb + SM_KV + 4 * KV_SLOT, 2 * KV_SLOT);
  if (lds32(sb + SM_MISC)) { stg32(&g_flags.kv0[s * 32 + 1], epoch + 1); __threadfence(); }
  ST_WAIT(" 0");
  flag_add_relaxed(&g_flags.kv0[s * 32]);
#pragma unroll 1
  for (int i = 0; i < 5; i++) asm volatile("prefetch.tensormap [%0];" ::"l"(&mp.wdm + i) : "memory");
  mbar_wait_watch(bar + 8 * B_IMG2, 0);
  flag_add(&g_flags.kv1[s * 32]);
  mbar_wait_watch(bar + 8 * B_Q, 0);
  flag_add(&g_flags.kq[s * 32]);
  flags_wait(&g_flags.g[0], epoch * 4 + 4);
  fence_async_global();
  ld_bulk(bar + 8 * B_GATE, 1024, sb + SM_G, g_gate + rb * 128);
  int hc = 0, oc = 0;
#pragma unroll 1
  for (int e = 0; e < 9; e++) {
    const bool ish = (0x6B >> e) & 1;
    mbar_wait_watch(bar + 8 * (ish ? B_HDONE + hc : B_ODONE + oc), 0);
    flag_add(ish ? &g_flags.h[(rb * 8 + s) * 8] : &g_flags.o[(rb * 4 + oc) * 8]);
    if (ish) hc++; else oc++;
    if (e >= 5) {
      const bool aux = e == 7 && lane >= 4;
      flags_wait(aux ? &g_flags.ao[s * 32] : e < 7 ? &g_flags.h[(rb * 8 + (s & 4) + (lane & 3)) * 8] : &g_flags.o[(rb * 4 + min(lane & 3, oc - 1)) * 8],
                 aux ? epoch + 1 : e < 7 ? epoch * 5 + 2 * e - 7 : epoch * 8 + 8);
      warp_arrive(bar + 8 * B_HOK);
    }
  }
  fence_async_global();
  const uint8_t* asrc = g_a2 + ((size_t)rb * NPLANE + 630) * 2048;
  mbar_wait_watch(bar + 8 * B_T, 0);
#pragma unroll
  for (int w = 0; w < 3; w++) {
    ld_bulk(bar + 8 * (B_FULL + w), 12288, sb + SM_X + (3 + w) * F2_SLOT, asrc + w * 12288);
  }
  if (lane == 0) g_flags.launch[blockIdx.x] = epoch + 1;
}

struct Ctx {
  uint32_t sb;
  int wg, rb, s;
  uint64_t kd, vd;
};
struct Att {
  float o[12];
  uint32_t p[16];
  uint32_t q[8];
  uint32_t qn[6];
};
template <int N> __device__ __forceinline__ void load_q(uint32_t (&q)[N], int id, int u) {
  const uint2* src = g_qs + (size_t)(id * 12 + u * 3) * 256 + tid_now();
  asm volatile("ld.global.cg.v2.u32 {%0, %1}, [%6];\nld.global.cg.v2.u32 {%2, %3}, [%6 + 2048];\nld.global.cg.v2.u32 {%4, %5}, [%6 + 4096];"
               : "=r"(q[0]), "=r"(q[1]), "=r"(q[2]), "=r"(q[3]), "=r"(q[4]), "=r"(q[5]) : "l"(src) : "memory");
}
__device__ __forceinline__ void next_q(Att& t) {
#pragma unroll
  for (int i = 0; i < 6; i++) asm volatile("mov.b32 %0, %1;" : "=r"(t.q[i]) : "r"(t.qn[i]));
}
template <int O> __device__ __forceinline__ void issue_qk(float (&s)[32], const uint32_t (&q)[8], uint64_t kd) {
  wgmma_rs0_n64<0, O>(s, q[0], q[1], q[2], q[3], kd);
  wgmma_rs1_n64<0, O + 128>(s, q[4], q[5], q[6], q[7], kd);
}
template <int O> __device__ __forceinline__ void issue_pv(float (&o)[12], const uint32_t (&p)[16], uint64_t vd, int keep) {
  wgmma_rs_n24<1, O>(o, p[0], p[1], p[2], p[3], vd, keep);
  wgmma_rs1_n24<1, O + 16>(o, p[4], p[5], p[6], p[7], vd);
  wgmma_rs1_n24<1, O + 32>(o, p[8], p[9], p[10], p[11], vd);
  wgmma_rs1_n24<1, O + 48>(o, p[12], p[13], p[14], p[15], vd);
}
template <int U> __device__ __forceinline__ void finish_head(const Ctx& c, const float (&o)[12]) {
  const int tid = tid_now(), r4 = (tid >> 5) * 64 + (tid & 28);
  const float i0 = __uint_as_float(lds32(c.sb + SM_G + 2 * r4)) * (U == 3 ? __uint_as_float(lds32(c.sb + SM_G + 4 + 2 * r4)) : 1.f) * rcp_fast(__shfl_sync(0xffffffffu, o[0], (U + 2) & 3, 4));
  const float i1 = __uint_as_float(lds32(c.sb + SM_G + 64 + 2 * r4)) * (U == 3 ? __uint_as_float(lds32(c.sb + SM_G + 68 + 2 * r4)) : 1.f) * rcp_fast(__shfl_sync(0xffffffffu, o[2], (U + 2) & 3, 4));
  uint8_t* base = g_a2 + ((size_t)c.rb * NPLANE + 576 + 18 * U) * 2048;
  const int p1 = (tid - U) & 3;
#pragma unroll
  for (int t = 0; t < 3; t++) {
    const uint32_t k = (t == 2 ? 100 : __byte_perm(t ? 0x62603432 : 0x30040200, 0, 0x4440 + p1)) + 6 * c.s;
    uint8_t* a = base + ((k >> 3) * 2032 + 2 * k + 4 * r4);
    const int r = t == 2 ? 0 : 4 + 4 * t;
    uint32_t v0 = pack2(o[r] * i0, o[r + 1] * i0), v1 = pack2(o[r + 2] * i1, o[r + 3] * i1);
    if (t == 2) { v0 = __shfl_sync(0xffffffffu, v0, (U + 1) & 3, 4); v1 = __shfl_sync(0xffffffffu, v1, (U + 1) & 3, 4); }
    stg32(a, v0); stg32(a + 128, v1);
  }
  warp_arrive(c.sb + SM_BAR + 8 * (B_ODONE + U));
}
__device__ __forceinline__ float geglu2(float x, float y) {
  const float t = tanh_fast(x * fmaf(x * x, 0.0356774081f, 0.7978845608f));
  const float w = x * y;
  return fmaf(w, t, w);
}
template <int G, int U, int N> __device__ __forceinline__ void geglu_block(float (&acc)[N], uint8_t* a, int zero) {
  if (zero != G + 1) {
#pragma unroll
    for (int j = 0; j < 8; j++) {
      stg32(a + j * 2048, pack2(geglu2(acc[G + 4 * j], acc[U + 4 * j]), geglu2(acc[G + 4 * j + 1], acc[U + 4 * j + 1])));
      stg32(a + j * 2048 + 128, pack2(geglu2(acc[G + 4 * j + 2], acc[U + 4 * j + 2]), geglu2(acc[G + 4 * j + 3], acc[U + 4 * j + 3])));
    }
  }
}
template <int OA, int OB, int NACC> __device__ __forceinline__ void issue_ffn(float (&acc)[NACC], uint64_t ad, uint64_t bd, int keep) {
  if constexpr (NACC == 128) {
    wgmma_ss_n256<1, OA, OB>(acc, ad, bd, keep);
    wgmma_ss1_n256<1, OA + 2, OB + 128>(acc, ad, bd);
  } else if constexpr (NACC == 64) {
    wgmma_ss1_n128<1, OA, OB>(acc, ad, bd);
    wgmma_ss1_n128<1, OA + 2, OB + 128>(acc, ad, bd);
    wgmma_ss1_n128<1, OA + 4, OB + 256>(acc, ad, bd);
    wgmma_ss1_n128<1, OA + 6, OB + 384>(acc, ad, bd);
  } else {
    wgmma_ss1_n144<1, OA, OB>(acc, ad, bd);
    wgmma_ss1_n144<1, OA + 256, OB + 128>(acc, ad, bd);
    wgmma_ss1_n144<1, OA + 512, OB + 256>(acc, ad, bd);
  }
}
struct NoOp { __device__ __forceinline__ void operator()() const {} };
constexpr int KS = KV_SLOT >> 4;
template <int OK, int OV, int OA, int OB, int FIN = -1, int NACC, class Mid>
__device__ __forceinline__ void att_step(const Ctx& c, Att& t, float (&acc)[NACC], uint64_t kd, uint64_t vd, uint64_t ad, uint64_t bd,
                                         uint32_t donebar, uint32_t rdonebar, uint32_t nextbar, int nphase, int keep, Mid mid, int pvkeep = 1, bool fin = false) {
  float s[32];
  pin(t.q); pin(t.p); pin(t.o); pin(acc);
  WG_FENCE();
  issue_pv<OV * KS>(t.o, t.p, vd, pvkeep);
  issue_qk<OK * KS>(s, t.q, kd);
  WG_COMMIT();
  issue_ffn<OA, OB>(acc, ad, bd, keep);
  WG_COMMIT();
  WG_WAIT(1);
  pin(s); pin(t.o); pin(t.p); pin(t.q);
  mid();
  if (FIN >= 0 && fin) {
#pragma unroll
    for (int i = 0; i < 16; i++) t.p[i] = pack2(ex2n(s[2 * i]), ex2n(s[2 * i + 1]));
    finish_head<FIN < 0 ? 0 : FIN>(c, t.o);
    pin(t.p);
    mbar_wait(nextbar, nphase);
  } else {
#pragma unroll
    for (int i = 0; i < 16; i++) t.p[i] = pack2(ex2(s[2 * i]), ex2(s[2 * i + 1]));
    pin(t.p);
    mbar_wait_early(nextbar, nphase);
  }
  WG_WAIT(0);
  pin(acc);
  warp_arrive_both(donebar, rdonebar);
}

template <class Extra>
__device__ __forceinline__ void att_only_step(Att& t, uint64_t kd, uint64_t vd, uint32_t donebar, uint32_t rdonebar, uint32_t nextbar, int nphase, Extra extra) {
  float s[32];
  pin(t.q); pin(t.p); pin(t.o);
  WG_FENCE();
  issue_pv<0>(t.o, t.p, vd, 1);
  issue_qk<0>(s, t.q, kd);
  WG_COMMIT();
  extra();
  WG_WAIT(0);
  pin(s); pin(t.o); pin(t.p); pin(t.q);
  warp_arrive_both(donebar, rdonebar);
#pragma unroll
  for (int i = 0; i < 16; i++) t.p[i] = pack2(ex2(s[2 * i]), ex2(s[2 * i + 1]));
  pin(t.p);
  mbar_wait_early(nextbar, nphase);
}
template <int U> __device__ __forceinline__ uint32_t x_plane(const uint32_t (&pk)[54], int q, int r) {
  const uint32_t v3 = __shfl_sync(0xffffffffu, pk[36 + 4 * U + 4 + r], U, 4);
  return q == U ? pk[18 + 4 * U + 4 + r] : q == ((U + 1) & 3) ? v3 : 0x3F803F80u;
}
template <int U> __device__ __forceinline__ uint32_t pair_of(const uint32_t (&pk)[54], int q, int ty, int i, int r) {
  return q >= U ? pk[18 * ty + 4 * U + 2 * i + r] : pk[18 * ty + 4 * U + 2 * i + 2 + r];
}
__device__ __forceinline__ uint32_t sq_add(uint32_t a, uint32_t c) { uint32_t d; asm("fma.rn.bf16x2 %0, %1, %1, %2;" : "=r"(d) : "r"(a), "r"(c)); return d; }
__device__ __forceinline__ uint32_t add2(uint32_t a, uint32_t b) { uint32_t d; asm("add.rn.bf16x2 %0, %1, %2;" : "=r"(d) : "r"(a), "r"(b)); return d; }
template <int TY> __device__ __forceinline__ float max_norm2(const uint32_t (&pk)[54], int q) {
  uint32_t mx = 0;
#pragma unroll
  for (int u = 0; u < 4; u++) {
    uint32_t n[2];
#pragma unroll
    for (int r = 0; r < 2; r++) {
      const int b = 18 * TY + 4 * u + r;
      n[r] = sq_add(pk[b + 2], 0u);
      if (q >= u) n[r] = sq_add(pk[b], n[r]);
      if (q <= u) n[r] = sq_add(pk[b + 4], n[r]);
    }
    uint32_t v = add2(__byte_perm(n[0], n[1], 0x5410), __byte_perm(n[0], n[1], 0x7632));
    v = add2(v, __shfl_xor_sync(0xffffffffu, v, 1));
    v = add2(v, __shfl_xor_sync(0xffffffffu, v, 2));
    asm("max.NaN.bf16x2 %0, %0, %1;" : "+r"(mx) : "r"(v));
  }
  return max_nan(bf_lo(mx), bf_hi(mx));
}
template <int U> __device__ __forceinline__ void store_kv(const uint32_t (&pk)[54], int q, uint8_t* a) {
#pragma unroll
  for (int r = 0; r < 2; r++) {
    uint8_t* p = a + U * 32 * KV_SLOT + r * 128;
    stg32(p, pair_of<U>(pk, q, 1, 0, r)); stg32(p + 1024, pair_of<U>(pk, q, 1, 1, r)); stg32(p + 2048, x_plane<U>(pk, q, r));
    stg32(p + 3072, pair_of<U>(pk, q, 2, 0, r)); stg32(p + 4096, pair_of<U>(pk, q, 2, 1, r));
  }
}
template <int U, int N> __device__ __forceinline__ void q_frag(const uint32_t (&pk)[54], int q, uint32_t (&f)[N]) {
#pragma unroll
  for (int r = 0; r < 2; r++) { f[r] = pair_of<U>(pk, q, 0, 0, r); f[2 + r] = pair_of<U>(pk, q, 0, 1, r); f[4 + r] = q == U ? pk[4 * U + 4 + r] : 0u; }
}

__device__ __forceinline__ void consumer(const Maps& mp, uint32_t sb, int rb, int s, int wg, uint64_t zero) {
  Ctx c;
  c.sb = sb; c.rb = rb; c.s = s; c.wg = wg;
  const uint32_t bar = sb + SM_BAR;
  const uint32_t rbar = peer_addr(bar, (rb & 1) ^ 1);
  const uint32_t xa = sb + SM_X + wg * 8192;
  Att t;
  uint32_t pk[54];
  {
    float am[96], ar[12];
#pragma unroll
    for (int i = 0; i < 96; i++) am[i] = 0.f;
#pragma unroll
    for (int i = 0; i < 12; i++) ar[i] = 0.f;
    pin(am); pin(ar);
    int slot = 2, prev = 0, ph = 0;
#pragma unroll 1
    for (int st = 0; st < 18; st++) {
      mbar_wait(bar + 8 * (B_AFULL + slot), ph);
      const uint64_t da = mkdesc(xa + (st >> 1) * 16384 + (st & 1) * 64, 16, 1024, 1);
      const uint64_t db = mkdesc(sb + SM_W + slot * 12288, 2048, 1024, 1), dr = mkdesc(sb + SM_AR + slot * 1536, 128, 256, 0);
      WG_FENCE();
      wgmma_ss1_n192<1, 0, 0>(am, da, db);
      wgmma_ss1_n24<1, 0, 0>(ar, da, dr);
      wgmma_ss1_n192<1, 2, 384>(am, da, db);
      wgmma_ss1_n24<1, 2, 48>(ar, da, dr);
      WG_COMMIT();
      WG_WAIT(1);
      if (st > 0) warp_arrive_both(bar + 8 * (B_AEMPTY + prev), rbar + 8 * (B_AEMPTY + prev));
      prev = slot;
      if (++slot == 5) slot = 0;
      if (slot == 2) ph ^= 1;
    }
    WG_WAIT(0);
    pin(am); pin(ar);
    asm volatile("setmaxnreg.inc.sync.aligned.u32 232;");
    const int tid = tid_now(), q = tid & 3;
#pragma unroll
    for (int i = 0; i < 54; i++) {
      const int ty = i / 18, j = i % 18 >> 1, r = i & 1;
      const float a = j < 8 ? am[(ty * 8 + j) * 4 + 2 * r] : ar[ty * 4 + 2 * r], b = j < 8 ? am[(ty * 8 + j) * 4 + 2 * r + 1] : ar[ty * 4 + 2 * r + 1];
      pk[i] = ty == 0 ? pack2(a * 0.34004648f, b * 0.34004648f) : pack2(a, b);
    }
    uint32_t v2 = 0;
#pragma unroll
    for (int i = 36; i < 54; i++) v2 = sq_add(pk[i], v2);
    const float nq = max_norm2<0>(pk, q), nk = max_norm2<1>(pk, q);
    if (!(nq <= 16.f && nk <= 138.f && bf_lo(v2) + bf_hi(v2) <= 1e24f)) sts32(sb + SM_MISC, 1u);
    const uint32_t img = sb + SM_KV + (4 + wg) * KV_SLOT + (tid & 96) * 8 + (tid & 15) * 16, hi = (tid & 16) * 64;
    stsm4(img + hi, pk[18], pk[19], pk[20], pk[21]);
    stsm4(img + hi + 3072, pk[36], pk[37], pk[38], pk[39]);
    asm volatile("stmatrix.sync.aligned.m8n8.x2.shared.b16 [%0], {%1, %2};" ::"r"(img + 2048), "r"(x_plane<0>(pk, q, 0)), "r"(x_plane<0>(pk, q, 1)) : "memory");
    fence_async_smem();
    warp_arrive(bar + 8 * B_IMG);
  }
  c.kd = mkdesc(sb + SM_KV, 1024, 128, 0) + zero; c.vd = mkdesc(sb + SM_KV + 2048, 128, 1024, 0) + zero;
  const uint64_t xd = mkdesc(xa, 16, 1024, 1) + zero, wd = mkdesc(sb + SM_W, 4096, 1024, 1) + zero;
  {
    float acc[128];
    pin(pk);
    mbar_wait_early(bar + 8 * B_FULL, 0);
    WG_FENCE();
    wgmma_ss0_n256<1, 0, 0>(acc, xd, wd);
    wgmma_ss1_n256<1, 2, 128>(acc, xd, wd);
    WG_COMMIT();
    const int tid0 = tid_now(), q = tid0 & 3;
    uint8_t* ka = g_kv + (size_t)(s * 128 + rb * 2 + wg) * KV_SLOT + ((tid0 & 96) * 8 + (tid0 & 31) * 4);
    uint2* qdst = g_qs + (size_t)(rb * 8 + s) * 12 * 256 + tid0;
#pragma unroll 1
    for (int n = 1; n < 6; n++) {
      mbar_wait(bar + 8 * (B_FULL + n), 0);
      WG_FENCE();
      issue_ffn<0, 0>(acc, xd + (n >> 1) * 1024 + (n & 1) * 4, wd + (n >= 3 ? n - 3 : n) * 1024, 1);
      WG_COMMIT();
      WG_WAIT(1);
      warp_arrive_both(bar + 8 * (B_DONE + n - 1), rbar + 8 * (B_DONE + n - 1));
      if (n & 2) { if (n & 1) store_kv<2>(pk, q, ka); else store_kv<1>(pk, q, ka); }
      else if (!(n & 1)) store_kv<3>(pk, q, ka);
    }
    warp_arrive(bar + 8 * B_IMG2);
    {
      uint32_t f[6];
      q_frag<2>(pk, q, f);
#pragma unroll
      for (int i = 0; i < 3; i++) qdst[(6 + i) * 256] = make_uint2(f[2 * i], f[2 * i + 1]);
      q_frag<3>(pk, q, f);
#pragma unroll
      for (int i = 0; i < 3; i++) qdst[(9 + i) * 256] = make_uint2(f[2 * i], f[2 * i + 1]);
    }
    q_frag<0>(pk, q, t.q); q_frag<1>(pk, q, t.qn);
    t.q[6] = tid0 & (int)zero; t.q[7] = (tid0 >> 1) & (int)zero;
    WG_WAIT(0);
    pin(acc);
    warp_arrive_both(bar + 8 * (B_DONE + 5), rbar + 8 * (B_DONE + 5));
    mbar_wait(bar + 8 * B_GO, 0);
    if (!__shfl_sync(0xffffffffu, lds32(sb + SM_MISC + 4), 0)) {
#pragma unroll
      for (int i = 0; i < 3; i++) { qdst[i * 256] = make_uint2(t.q[2 * i], t.q[2 * i + 1]); qdst[(3 + i) * 256] = make_uint2(t.qn[2 * i], t.qn[2 * i + 1]); }
#pragma unroll 1
      for (int u = 0; u < 4; u++) {
        load_q(t.q, rb * 8 + s, u);
        float m[2] = {-INFINITY, -INFINITY};
#pragma unroll 1
        for (int i = 0; i < 32; i++) {
          float sv[32];
          mbar_wait(bar + 8 * (B_PFULL + (i & 1)), i >> 1 & 1);
          pin(t.q);
          WG_FENCE();
          issue_qk<4 * KS>(sv, t.q, c.kd + (i & 1) * KS);
          WG_COMMIT();
          WG_WAIT(0);
          pin(sv);
          warp_arrive(bar + 8 * (B_PEMPTY + (i & 1)));
#pragma unroll
          for (int k = 0; k < 32; k++) m[(k >> 1) & 1] = fmaxf(m[(k >> 1) & 1], sv[k]);
        }
        const int p1 = (tid_now() - u) & 3;
        uint32_t w[2];
#pragma unroll
        for (int r = 0; r < 2; r++) {
          float v = fmaxf(m[r], __shfl_xor_sync(0xffffffffu, m[r], 1));
          v = -fmaxf(v, __shfl_xor_sync(0xffffffffu, v, 2));
          const float a = bf_lo(pack2(v, 0.f)), b = bf_lo(pack2(v - a, 0.f));
          const uint32_t w2 = pack2(a, b), w3 = pack2(v - a - b, 0.f);
          w[r] = p1 == 2 ? w2 : p1 == 3 ? w3 : t.q[4 + r];
        }
        qdst[(u * 3 + 2) * 256] = make_uint2(w[0], w[1]);
      }
      load_q(t.q, rb * 8 + s, 0); load_q(t.qn, rb * 8 + s, 1);
    }
    warp_arrive(bar + 8 * B_Q);
#pragma unroll
    for (int i = 0; i < 16; i++) t.p[i] = 0;
#pragma unroll
    for (int i = 0; i < 12; i++) t.o[i] = 0.f;
    mbar_wait(bar + 8 * B_FULL, 1);
    int it = 1;
#pragma unroll 1
    for (int ft = 0; ft < 4; ft++) {
      uint64_t xi = xd + (ft == 0 ? 3072 : 0);
#pragma unroll 1
      for (int i3 = ft == 0; i3 < 3; i3++, it++, xi += 3072) {
        const int ph = it & 1;
        att_step<0, 5, 0, 0>(c, t, acc, c.kd, c.vd, xi, wd, bar + 8 * (B_DONE + 0), rbar + 8 * (B_DONE + 0), bar + 8 * (B_FULL + 1), ph, i3 != 0, NoOp());
        att_step<1, 0, 4, 1024>(c, t, acc, c.kd, c.vd, xi, wd, bar + 8 * (B_DONE + 1), rbar + 8 * (B_DONE + 1), bar + 8 * (B_FULL + 2), ph, 1, [&] { if (it == 6) next_q(t); });
        att_step<2, 1, 1024, 2048, 0>(c, t, acc, c.kd, c.vd, xi, wd, bar + 8 * (B_DONE + 2), rbar + 8 * (B_DONE + 2), bar + 8 * (B_FULL + 3), ph, 1, NoOp(), 1, it == 6);
        att_step<3, 2, 1028, 0>(c, t, acc, c.kd, c.vd, xi, wd, bar + 8 * (B_DONE + 3), rbar + 8 * (B_DONE + 3), bar + 8 * (B_FULL + 4), ph, 1, [&] { if (it == 11) next_q(t); }, it != 6);
        att_step<4, 3, 2048, 1024, 1>(c, t, acc, c.kd, c.vd, xi, wd, bar + 8 * (B_DONE + 4), rbar + 8 * (B_DONE + 4), bar + 8 * (B_FULL + 5), ph, 1, NoOp(), 1, it == 11);
        att_step<5, 4, 2052, 2048>(c, t, acc, c.kd, c.vd, xi, wd, bar + 8 * (B_DONE + 5), rbar + 8 * (B_DONE + 5), bar + 8 * (B_FULL + 0), ph ^ 1, 1, NoOp(), it != 11);
      }
      if (ft == 1) mbar_wait(bar + 8 * B_GATE, 0);
      if (ft & 2) load_q(t.qn, rb * 8 + s, ft);
      const int tid = tid_now();
      uint8_t* a = g_a2 + ((size_t)rb * NPLANE + 72 * s + 16 * ft) * 2048 + ((tid >> 5) * 256 + (tid & 31) * 4);
      geglu_block<0, 64>(acc, a, (int)zero);
      geglu_block<32, 96>(acc, a + 8 * 2048, (int)zero);
      warp_arrive(bar + 8 * (B_HDONE + ft));
    }
  }
  {
    int slot = 0, prev = 5, w3 = 0;
    float acch[64];
#pragma unroll
    for (int i = 0; i < 64; i++) acch[i] = 0.f;
#pragma unroll 1
    for (int kb = 0; kb < 9; kb++) {
      const int next = slot == 5 ? 0 : slot + 1;
      att_step<0, 0, 0, (256 << 16)>(c, t, acch, c.kd + slot * KS, c.vd + prev * KS, xd + kb * 1024, wd + w3 * 1024,
                                     bar + 8 * (B_DONE + slot), rbar + 8 * (B_DONE + slot), bar + 8 * (B_FULL + next), kb >= 5, 1, NoOp());
      prev = slot; slot = next;
      if (++w3 == 3) w3 = 0;
    }
    const int tid = tid_now();
    geglu_block<0, 32>(acch, g_a2 + ((size_t)rb * NPLANE + 72 * s + 64) * 2048 + ((tid >> 5) * 256 + (tid & 31) * 4), (int)zero);
    warp_arrive(bar + 8 * (B_HDONE + 4));
  }
  float acc[72];
#pragma unroll
  for (int i = 0; i < 72; i++) acc[i] = 0.f;
  constexpr int FS = F2_SLOT >> 4;
  const uint64_t fa = mkdesc(sb + SM_X + wg * 1024, 2048, 128, 0) + zero, fb = mkdesc(sb + SM_X + 12288, 6144, 1024, 1) + zero;
  const uint64_t kd2 = c.kd + zero, vd2 = c.vd + zero;
  const bool fin = wg == s >> 2;
#pragma unroll 1
  for (int it = 0;; it++) {
    const int ph = it & 1;
    if (it == 8 && !fin) {
      att_only_step(t, c.kd + 3 * KS, c.vd + 2 * KS, bar + 8 * (B_DONE + 3), rbar + 8 * (B_DONE + 3), bar + 8 * (B_FULL + 4), 1, [&] {
        uint4* part = g_part + (size_t)((rb * 4 + (s & 3)) * 2 + wg) * 9 * 128 + (tid_now() & 127);
#pragma unroll
        for (int i = 0; i < 9; i++)
          part[i * 128] = make_uint4(pack2(acc[8 * i], acc[8 * i + 1]), pack2(acc[8 * i + 2], acc[8 * i + 3]), pack2(acc[8 * i + 4], acc[8 * i + 5]), pack2(acc[8 * i + 6], acc[8 * i + 7]));
        warp_arrive2(bar + 8 * B_PDONE);
      });
      int slot = 4, prev = 3;
#pragma unroll 1
      for (int n = 0; n < 2; n++) {
        const int next = slot == 5 ? 0 : slot + 1;
        att_only_step(t, c.kd + slot * KS, c.vd + prev * KS, bar + 8 * (B_DONE + slot), rbar + 8 * (B_DONE + slot), bar + 8 * (B_FULL + next), n == 0, NoOp());
        prev = slot; slot = next;
      }
      break;
    }
    att_step<3, 2, 0, 0>(c, t, acc, kd2, vd2, fa, fb, bar + 8 * (B_DONE + 3), rbar + 8 * (B_DONE + 3), bar + 8 * (B_FULL + 4), ph ^ 1, 1, NoOp());
    att_step<4, 3, FS, FS>(c, t, acc, kd2, vd2, fa, fb, bar + 8 * (B_DONE + 4), rbar + 8 * (B_DONE + 4), bar + 8 * (B_FULL + 5), ph ^ 1, 1, NoOp());
    att_step<5, 4, 2 * FS, 2 * FS>(c, t, acc, kd2, vd2, fa, fb, bar + 8 * (B_DONE + 5), rbar + 8 * (B_DONE + 5), bar + 8 * (B_FULL + 0), ph, 1, [&] { if (it == 3) next_q(t); });
    if (it == 8) break;
    att_step<0, 5, 3 * FS, 3 * FS, 2>(c, t, acc, kd2, vd2, fa, fb, bar + 8 * (B_DONE + 0), rbar + 8 * (B_DONE + 0), bar + 8 * (B_FULL + 1), ph, 1, NoOp(), 1, it == 3);
    att_step<1, 0, 4 * FS, 4 * FS>(c, t, acc, kd2, vd2, fa, fb, bar + 8 * (B_DONE + 1), rbar + 8 * (B_DONE + 1), bar + 8 * (B_FULL + 2), ph, 1, NoOp(), it != 3);
    att_step<2, 1, 5 * FS, 5 * FS>(c, t, acc, kd2, vd2, fa, fb, bar + 8 * (B_DONE + 2), rbar + 8 * (B_DONE + 2), bar + 8 * (B_FULL + 3), ph, 1, NoOp());
  }
  pin(t.p); pin(t.o);
  WG_FENCE();
  issue_pv<5 * KS>(t.o, t.p, c.vd, 1);
  WG_COMMIT();
  float ao[12];
#pragma unroll
  for (int i = 0; i < 3; i++)
    asm volatile("ld.shared.v4.f32 {%0, %1, %2, %3}, [%4];" : "=f"(ao[4 * i]), "=f"(ao[4 * i + 1]), "=f"(ao[4 * i + 2]), "=f"(ao[4 * i + 3])
                 : "r"(sb + SM_AO + i * 4096 + tid_now() * 16) : "memory");
  WG_WAIT(0);
  pin(t.o);
#pragma unroll
  for (int i = 0; i < 12; i++) t.o[i] += ao[i];
  finish_head<3>(c, t.o);
  if (!fin) return;
  const int tid = tid_now();
  const uint4* part = g_part + (size_t)((rb * 4 + (s & 3)) * 2 + wg) * 9 * 128 + (tid & 127);
  const uint32_t ga = sb + SM_G + 4 + (tid >> 5) * 128 + (tid & 28) * 2;
  const float c0 = __uint_as_float(lds32(ga)), c1 = __uint_as_float(lds32(ga + 64));
  uint4 pv[9];
  pin(acc);
#pragma unroll 1
  for (int w = 3; w < 12; w++) {
    const int fs = w < 6 ? w : w - 6;
    if (w == 9) {
      mbar_wait(bar + 8 * B_POK, 0);
#pragma unroll
      for (int i = 0; i < 9; i++) pv[i] = __ldcg(part + i * 128);
      WG_WAIT(0);
      pin(acc);
#pragma unroll
      for (int i = 0; i < 9; i++) {
        acc[8 * i] = (acc[8 * i] + bf_lo(pv[i].x)) * c0; acc[8 * i + 1] = (acc[8 * i + 1] + bf_hi(pv[i].x)) * c0;
        acc[8 * i + 2] = (acc[8 * i + 2] + bf_lo(pv[i].y)) * c1; acc[8 * i + 3] = (acc[8 * i + 3] + bf_hi(pv[i].y)) * c1;
        acc[8 * i + 4] = (acc[8 * i + 4] + bf_lo(pv[i].z)) * c0; acc[8 * i + 5] = (acc[8 * i + 5] + bf_hi(pv[i].z)) * c0;
        acc[8 * i + 6] = (acc[8 * i + 6] + bf_lo(pv[i].w)) * c1; acc[8 * i + 7] = (acc[8 * i + 7] + bf_hi(pv[i].w)) * c1;
      }
      pin(acc);
    }
    mbar_wait(bar + 8 * (B_FULL + (w < 9 ? w - 3 : w - 9)), w >= 9);
    WG_FENCE();
    issue_ffn<0, 0>(acc, fa + fs * FS, fb + fs * FS, 1);
    WG_COMMIT();
    if (w >= 4 && w <= 6) {
      WG_WAIT(1);
      warp_arrive_both(bar + 8 * (B_DONE + w - 4), rbar + 8 * (B_DONE + w - 4)); warp_arrive_both(bar + 8 * (B_DONE + w - 4), rbar + 8 * (B_DONE + w - 4));
      if (w == 6) warp_arrive2(bar + 8 * B_T);
    }
  }
  WG_WAIT(0);
  pin(acc);
  const uint32_t stage = sb + SM_KV + ((tid >> 5) & 3) * 4608;
#pragma unroll
  for (int i = 0; i < 9; i++)
    stsm4(stage + (tid & 15) * 288 + ((tid >> 4) & 1) * 16 + i * 32, pack2(acc[8 * i], acc[8 * i + 1]), pack2(acc[8 * i + 2], acc[8 * i + 3]),
          pack2(acc[8 * i + 4], acc[8 * i + 5]), pack2(acc[8 * i + 6], acc[8 * i + 7]));
  fence_async_smem();
  __syncwarp();
  const int wu = __shfl_sync(0xffffffffu, tid >> 5, 0);
  asm volatile(ELECT "@p cp.async.bulk.tensor.2d.global.shared::cta.bulk_group [%0, {%1, %2}], [%3];\n@p cp.async.bulk.commit_group;\n@p cp.async.bulk.wait_group.read 0;\n}"
               ::"l"(&mp.out), "r"((s & 3) * 144), "r"(rb * 128 + wu * 16), "r"(sb + SM_KV + (wu & 3) * 4608) : "memory");
}

__device__ __forceinline__ void aux_gate(const __nv_bfloat16* __restrict__ x, const __nv_bfloat16* __restrict__ gw) {
  const int lane = threadIdx.x & 31, l8 = lane & 7;
  const int row0 = (blockIdx.x - NMAIN) * 512 + (threadIdx.x >> 5) * 64 + (lane >> 3);
  uint4 w[9];
#pragma unroll
  for (int i = 0; i < 9; i++) w[i] = __ldg((const uint4*)gw + l8 + 8 * i);
#pragma unroll 1
  for (int p = 0; p < 16; p++) {
    const uint4* xr = (const uint4*)(x + (size_t)(row0 + 4 * p) * 576) + l8;
    float a = 0.f;
#pragma unroll
    for (int i = 0; i < 9; i++) {
      const uint4 v = __ldg(xr + 8 * i);
      a = fmaf(bf_lo(v.x), bf_lo(w[i].x), a); a = fmaf(bf_hi(v.x), bf_hi(w[i].x), a);
      a = fmaf(bf_lo(v.y), bf_lo(w[i].y), a); a = fmaf(bf_hi(v.y), bf_hi(w[i].y), a);
      a = fmaf(bf_lo(v.z), bf_lo(w[i].z), a); a = fmaf(bf_hi(v.z), bf_hi(w[i].z), a);
      a = fmaf(bf_lo(v.w), bf_lo(w[i].w), a); a = fmaf(bf_hi(v.w), bf_hi(w[i].w), a);
    }
    a += __shfl_xor_sync(0xffffffffu, a, 1); a += __shfl_xor_sync(0xffffffffu, a, 2); a += __shfl_xor_sync(0xffffffffu, a, 4);
    const float e = __expf(-fabsf(a)), big = __fdividef(1.f, 1.f + e), small = e * big;
    const float g = a >= 0.f ? big : small, cc = max_nan(0.5f * (a >= 0.f ? small : big), 4.6566e-10f);
    if (l8 == 0) g_gate[row0 + 4 * p] = make_float2(__fdividef(g, cc), cc);
  }
  asm volatile("bar.sync 1, 256;" ::: "memory");
  if (threadIdx.x < 32) flag_add(&g_flags.g[0]);
}
__device__ __forceinline__ void aux_attention(uint32_t sb, int warp) {
  const uint32_t bar = sb + SM_BAR;
  const unsigned epoch = __ldcg(&g_launch_aux[blockIdx.x - NMAIN]);
  const uint64_t kd = mkdesc(sb, 1024, 128, 0), vd = mkdesc(sb + 2048, 128, 1024, 0);
  if (warp == 0) { warp_init(bar, 1); fence_async_smem(); }
#pragma unroll 1
  for (int i = 0; i < 2; i++) {
    const int s = (blockIdx.x - NMAIN) * 2 + i;
    flags_wait(&g_flags.kq[s * 32], epoch * 16 + 16);
    asm volatile("bar.sync 1, 256;" ::: "memory");
    if (warp == 0) { fence_async_global(); ld_bulk(bar, 2 * KV_SLOT, sb, g_kv + (size_t)(s * 128 + 126) * KV_SLOT); }
    uint32_t q[8];
    load_q(q, s, 3);
    mbar_wait(bar, i);
#pragma unroll 1
    for (int rb = 0; rb < 16; rb++) {
      uint32_t p0[16], p1[16];
      float s0[32], s1[32], o[12];
      q[6] = 0; q[7] = 0;
#pragma unroll
      for (int k = 0; k < 12; k++) o[k] = 0.f;
      pin(q); pin(o);
      WG_FENCE();
      issue_qk<0>(s0, q, kd);
      issue_qk<KS>(s1, q, kd);
      WG_COMMIT();
      WG_WAIT(0);
      pin(s0); pin(s1); pin(q);
      load_q(q, min(rb + 1, 15) * 8 + s, 3);
#pragma unroll
      for (int k = 0; k < 16; k++) { p0[k] = pack2(ex2(s0[2 * k]), ex2(s0[2 * k + 1])); p1[k] = pack2(ex2(s1[2 * k]), ex2(s1[2 * k + 1])); }
      pin(p0); pin(p1);
      WG_FENCE();
      issue_pv<0>(o, p0, vd, 1);
      issue_pv<KS>(o, p1, vd, 1);
      WG_COMMIT();
      WG_WAIT(0);
      pin(o);
      float4* dst = g_ao + (rb * 8 + s) * 768 + threadIdx.x;
#pragma unroll
      for (int k = 0; k < 3; k++) dst[k * 256] = make_float4(o[4 * k], o[4 * k + 1], o[4 * k + 2], o[4 * k + 3]);
    }
    asm volatile("bar.sync 1, 256;" ::: "memory");
    if (warp == 0) flag_add(&g_flags.ao[s * 32]);
  }
  if (threadIdx.x == 0) g_launch_aux[blockIdx.x - NMAIN] = epoch + 1;
}

__global__ void __cluster_dims__(2, 1, 1) __launch_bounds__(NTHREADS, 1)
fused_kernel(const __nv_bfloat16* __restrict__ x, const uint8_t* __restrict__ wqkv, uint64_t zero, const uint8_t* __restrict__ wd,
             const uint8_t* __restrict__ wo, const __nv_bfloat16* __restrict__ gw, const __grid_constant__ Maps mp) {
  extern __shared__ __align__(1024) uint8_t smem[];
  const uint32_t sb = (uint32_t)__cvta_generic_to_shared(smem);
  const int cl = blockIdx.x >> 1;
  const int role = cl < 4 ? 32 + 8 * cl : cl - 4 + max(0, (cl - 29) * 37 >> 8);
  const int s = role >> 3 & 7, rb = (role & 7) * 2 + (blockIdx.x & 1);
  const int warp = __shfl_sync(0xffffffffu, (int)(threadIdx.x >> 5), 0), lane = threadIdx.x & 31;
  if (blockIdx.x >= NMAIN) {
    if (warp < 8) { aux_gate(x, gw); aux_attention(sb, warp); }
    return;
  }
  if (warp < 3) {
    asm volatile("prefetch.tensormap [%0];" ::"l"(&mp.x + warp) : "memory");
    if (lane < 16) asm volatile("prefetch.global.L2 [%0];" ::"l"(x + (rb * 128 + s * 16 + lane) * 576 + warp * 64) : "memory");
  } else if (warp == 3) pf_bulk(wqkv + blockIdx.x * 4320, 4320);
  warp_init(sb + SM_BAR + 8 * warp, warp < B_AFULL ? 16 : warp < B_GO ? 2 : 1);
  if (warp == B_AFULL + 2) { fence_async_smem(); ld_2d_only(sb + SM_BAR + 8 * warp, sb + SM_X, &mp.x, 0, rb * 128); }
  warp_init(sb + SM_BAR + 8 * (12 + warp), warp < 6 ? 16 : warp < 11 ? 8 : 1);
  warp_init(sb + SM_BAR + 8 * (24 + warp), warp < 6 ? 3 - (warp & 1) : warp < 10 ? 1 : 8);
  warp_init(sb + SM_BAR + 8 * (36 + warp), 8);
  sts32(sb + SM_MISC, 0u);
  asm volatile("fence.mbarrier_init.release.cluster;\nbarrier.cluster.arrive.relaxed.aligned;" ::: "memory");
  fence_async_smem();
  __syncthreads();
  asm volatile("barrier.cluster.wait.aligned;" ::: "memory");
  if (warp < 8) {
    consumer(mp, sb, rb, s, warp >> 2, zero);
  } else {
    asm volatile("setmaxnreg.dec.sync.aligned.u32 40;");
    if (warp == 9) producer_kv(mp, wd, wo, sb, rb, s);
    else if (warp == 11) {
      publisher(mp, sb, rb, s, lane);
    } else producer_w(mp, wqkv, sb, rb, s, (warp >> 1) & 1);
  }
}

typedef CUresult (*EncodeFn)(CUtensorMap*, CUtensorMapDataType, cuuint32_t, void*, const cuuint64_t*, const cuuint64_t*, const cuuint32_t*,
                             const cuuint32_t*, CUtensorMapInterleave, CUtensorMapSwizzle, CUtensorMapL2promotion, CUtensorMapFloatOOBfill);
struct Dim { cuuint64_t size, stride; cuuint32_t box; };
void encode(EncodeFn fn, CUtensorMap* m, const void* base, CUtensorMapSwizzle sw, int rank, Dim a, Dim b, Dim c = {1, 0, 1}, Dim d = {1, 0, 1}) {
  cuuint64_t dims[4] = {a.size, b.size, c.size, d.size}, strides[3] = {b.stride, c.stride, d.stride};
  cuuint32_t box[4] = {a.box, b.box, c.box, d.box}, es[4] = {1, 1, 1, 1};
  CUresult r = fn(m, CU_TENSOR_MAP_DATA_TYPE_BFLOAT16, rank, const_cast<void*>(base), dims, strides, box, es, CU_TENSOR_MAP_INTERLEAVE_NONE, sw,
                  CU_TENSOR_MAP_L2_PROMOTION_L2_128B, CU_TENSOR_MAP_FLOAT_OOB_FILL_NONE);
  if (r != CUDA_SUCCESS) fprintf(stderr, "cuTensorMapEncodeTiled failed: %d\n", (int)r);
}

}

extern "C" void kernel_launch(void* const* d_in, const int* in_sizes, int n_in, void* d_out, int out_size) {
  (void)in_sizes; (void)n_in; (void)out_size;
  const void *x = d_in[0], *wqkv = d_in[1], *wo = d_in[2], *wg = d_in[4], *wu = d_in[5], *wd = d_in[6], *gw = d_in[7];
  static EncodeFn fn = nullptr;
  if (!fn) {
    cudaDriverEntryPointQueryResult qr;
    cudaGetDriverEntryPoint("cuTensorMapEncodeTiled", (void**)&fn, cudaEnableDefault, &qr);
    cudaFuncSetAttribute(fused_kernel, cudaFuncAttributeMaxDynamicSharedMemorySize, SM_TOTAL);
  }
  Maps mp;
  const CUtensorMapSwizzle S128 = CU_TENSOR_MAP_SWIZZLE_128B, S0 = CU_TENSOR_MAP_SWIZZLE_NONE;
  encode(fn, &mp.x, x, S128, 2, {576, 0, 64}, {2048, 1152, 128});
  encode(fn, &mp.qm, wqkv, S128, 3, {576, 0, 64}, {576, 3456, 16}, {3, 1152, 3});
  encode(fn, &mp.qr, wqkv, S0, 3, {576, 0, 8}, {576, 3456, 16}, {3, 1152, 3});
  encode(fn, &mp.wg, wg, S128, 2, {4608, 0, 64}, {576, 9216, 32});
  encode(fn, &mp.wu, wu, S128, 2, {4608, 0, 64}, {576, 9216, 32});
  encode(fn, &mp.wgh, wg, S128, 2, {4608, 0, 64}, {576, 9216, 64});
  encode(fn, &mp.wuh, wu, S128, 2, {4608, 0, 64}, {576, 9216, 64});
  encode(fn, &mp.wdm, wd, S128, 3, {576, 0, 64}, {6, 1152, 6}, {768, 6912, 8});
  encode(fn, &mp.wdn, wd, S128, 3, {576, 0, 16}, {6, 1152, 6}, {768, 6912, 4});
  encode(fn, &mp.wom, wo, S128, 3, {576, 0, 64}, {72, 1152, 6}, {8, 82944, 8});
  encode(fn, &mp.won, wo, S128, 3, {576, 0, 16}, {72, 1152, 6}, {8, 82944, 4});
  encode(fn, &mp.out, d_out, S0, 2, {576, 0, 144}, {2048, 1152, 16});
  fused_kernel<<<NCTA, NTHREADS, SM_TOTAL>>>((const __nv_bfloat16*)x, (const uint8_t*)wqkv, 0, (const uint8_t*)wd, (const uint8_t*)wo,
                                             (const __nv_bfloat16*)gw, mp);
}
```
